```python
import torch

def _softmax(x, axis=-1):
    return torch.softmax(x, dim=axis)

def _gelu(x):
    return torch.nn.functional.gelu(x, approximate='tanh')

def _silu(x):
    return torch.nn.functional.silu(x)

def _sigmoid(x):
    return torch.sigmoid(x)

def _layernorm(x, axis=-1, eps=1e-05):
    m = x.mean(dim=axis, keepdim=True)
    v = x.var(dim=axis, keepdim=True, unbiased=False)
    return (x - m) / torch.sqrt(v + eps)

def _scatter_add(tgt, idx, src, axis=0):
    return tgt.clone().index_add_(axis, idx, src)

def _segment_sum(src, seg, n):
    out = torch.zeros((n,) + src.shape[1:], dtype=src.dtype)
    return out.index_add_(0, seg, src)

def _pad(x, pw):
    flat = tuple((v for pair in reversed(pw) for v in pair))
    return torch.nn.functional.pad(x, flat)
kernel_name = 'adaLN_cond__ssm_conv_s4__mixer_gmlp__prompt'

def setup_inputs():

    _w = lambda a: (lambda t: t.to(torch.bfloat16) if t.is_floating_point() else t)(torch.as_tensor(a))

    def _A_setup():
        B, L, D, N = (1, 2048, 448, 256)
        A_re = -(lambda _x: torch.exp(torch.as_tensor(_x)))((lambda *s: torch.randn(*s, dtype=torch.bfloat16) * 3.2)(D, N))
        A_im = torch.pi * (lambda *s: torch.randn(*s, dtype=torch.bfloat16) * 0.1)(D, N)
        B_re = (lambda *s: torch.randn(*s, dtype=torch.bfloat16) * 0.2)(D, N)
        B_im = (lambda *s: torch.randn(*s, dtype=torch.bfloat16) * 0.2)(D, N)
        C_re = (lambda *s: torch.randn(*s, dtype=torch.bfloat16) * 0.1)(D, N)
        C_im = (lambda *s: torch.randn(*s, dtype=torch.bfloat16) * 0.2)(D, N)
        log_dt = (lambda *s: torch.randn(*s, dtype=torch.bfloat16) * 0.1)(D) * 0.5 - 4.0
        Dskip = (lambda *s: torch.randn(*s, dtype=torch.bfloat16) * 0.1)(D)
        return {'u': _w((lambda *s: torch.randn(*s, dtype=torch.bfloat16) * 0.05)(B, L, D)), 'A_re': _w(A_re), 'A_im': _w(A_im), 'B_re': _w(B_re), 'B_im': _w(B_im), 'C_re': _w(C_re), 'C_im': _w(C_im), 'log_dt': _w(log_dt), 'Dskip': _w(Dskip)}
    _A_in = _A_setup()

    def _B_setup():
        B, S, D, F = (1, 2048, 448, 1792)
        Fh = F // 2
        return {'x': _w((lambda *s: torch.randn(*s, dtype=torch.bfloat16) * 0.05)(B, S, D)), 'w_in': _w((lambda *s: torch.randn(*s, dtype=torch.bfloat16) * 0.4)(D, 2 * Fh)), 'w_sp': _w(0.01 * (lambda *s: torch.randn(*s, dtype=torch.bfloat16) * 0.4)(S, S)), 'b_sp': _w(1.0 + 0.01 * (lambda *s: torch.randn(*s, dtype=torch.bfloat16) * 0.05)(S)), 'w_out': _w((lambda *s: torch.randn(*s, dtype=torch.bfloat16) * 0.05)(Fh, D))}
    _B_in = _B_setup()
    return {'A_u': _A_in['u'], 'A_A_re': _A_in['A_re'], 'A_A_im': _A_in['A_im'], 'A_B_re': _A_in['B_re'], 'A_B_im': _A_in['B_im'], 'A_C_re': _A_in['C_re'], 'A_C_im': _A_in['C_im'], 'A_log_dt': _A_in['log_dt'], 'A_Dskip': _A_in['Dskip'], 'B_x': _B_in['x'], 'B_w_in': _B_in['w_in'], 'B_w_sp': _B_in['w_sp'], 'B_b_sp': _B_in['b_sp'], 'B_w_out': _B_in['w_out'], 'c': _w((lambda *s: torch.randn(*s, dtype=torch.bfloat16) * 0.2)(1, 448) * 8.0), 'w_mod': _w((lambda *s: torch.randn(*s, dtype=torch.bfloat16) * 0.2)(448, 6 * 448) * 448 ** (-0.5) * 8.0)}

def reference(A_u, A_A_re, A_A_im, A_B_re, A_B_im, A_C_re, A_C_im, A_log_dt, A_Dskip, B_x, B_w_in, B_w_sp, B_b_sp, B_w_out, c, w_mod):

    def _A_ref(u, A_re, A_im, B_re, B_im, C_re, C_im, log_dt, Dskip):
        Bsz, L, D = u.shape
        dt = torch.exp(log_dt)[:, None]
        A = A_re + 1j * A_im
        Bc = B_re + 1j * B_im
        Cc = C_re + 1j * C_im
        logdA = dt * A
        dB = dt * Bc
        l = (lambda x, dt: x.to(dt))(torch.arange(L), A_re.dtype)
        P = torch.exp(logdA[:, :, None] * l[None, None, :])
        K = torch.einsum('dn,dnl,dn->dl', Cc, P, dB).real
        L2 = 2 * L
        Kp = _pad(K, ((0, 0), (0, L)))
        up = (lambda x, *d: x.permute(*d))(u, 0, 2, 1)
        up = _pad(up, ((0, 0), (0, 0), (0, L)))
        Kf = (lambda x, axes=(-2, -1): torch.fft.rfft2(x.float(), dim=axes))(Kp[:, None, :], axes=(-2, -1))
        Uf = (lambda x, axes=(-2, -1): torch.fft.rfft2(x.float(), dim=axes))(up[:, :, None, :], axes=(-2, -1))
        Yf = Uf * Kf[None, :, :, :]
        y = (lambda x, s, axes=(-2, -1): torch.fft.irfft2(x, s=s, dim=axes).to(torch.bfloat16))(Yf, (1, L2), axes=(-2, -1))[:, :, 0, :L]
        y = (lambda x, *d: x.permute(*d))(y, 0, 2, 1) + u * Dskip[None, None, :]
        return y

    def _B_ref(x, w_in, w_sp, b_sp, w_out):
        B, S, D = x.shape
        F = w_in.shape[-1]
        Fh = F // 2
        z = _gelu(torch.einsum('bsd,df->bsf', x, w_in))
        z1 = z[..., :Fh].clone()
        z2 = _layernorm(z[..., Fh:], axis=-1)
        g = torch.einsum('ts,bsf->btf', w_sp, z2) + b_sp[None, :, None]
        return torch.einsum('bsf,fd->bsd', z1 * g, w_out)
    x = A_u
    mod = (_silu(c) @ w_mod).reshape(c.shape[0], 6, 1, -1)
    sa, ca, ga, sb, cb, gb = (mod[:, 0].clone(), mod[:, 1].clone(), mod[:, 2].clone(), mod[:, 3].clone(), mod[:, 4].clone(), mod[:, 5].clone())
    h = _layernorm(x, axis=-1) * (1 + ca) + sa
    x = x + ga * _A_ref(h, A_A_re, A_A_im, A_B_re, A_B_im, A_C_re, A_C_im, A_log_dt, A_Dskip)
    h = _layernorm(x, axis=-1) * (1 + cb) + sb
    x = x + gb * _B_ref(h, B_w_in, B_w_sp, B_b_sp, B_w_out)
    return x
```

```cpp
#include <cuda_runtime.h>
#include <cuda.h>
#include <cuda_bf16.h>
#include <stdint.h>

namespace {

constexpr int SEQ = 2048, DM = 448, NMODE = 256, FF = 1792, FH = 896;
constexpr int NCTA = 128, NCONV = 112, NTHREADS = 384;
constexpr int NA = 7, NB = 5;
constexpr uint32_t A_SLOT = 16384, B_SLOT = 14336;
constexpr uint32_t OFF_A = 0;
constexpr uint32_t OFF_B = OFF_A + NA * A_SLOT;
constexpr uint32_t OFF_STG = OFF_B + NB * B_SLOT;
constexpr uint32_t OFF_MISC = OFF_STG + 28672;
constexpr uint32_t SMEM_BYTES = 232448;
constexpr uint32_t GEN_PITCH = 144, GEN_BYTES = 56 * GEN_PITCH;
constexpr uint32_t OFF_GEN01 = 0;
constexpr uint32_t OFF_GEN2 = OFF_B;
constexpr uint32_t OFF_RED = 49152;
constexpr uint32_t KTAB_CH = 2080 * 4, KTAB_ODD = 1040 * 4;
constexpr uint32_t OFF_KTAB = OFF_B - 4 * KTAB_CH;
constexpr uint32_t H_HI = 2240, H_CH = 4480;
constexpr uint32_t OFF_H = OFF_STG;
constexpr uint32_t OFF_X = OFF_MISC + 1024;
constexpr uint32_t OFF_BAR = OFF_MISC;
constexpr uint32_t OFF_T0 = OFF_MISC + 1024;
constexpr uint32_t OFF_CSB = OFF_T0;
constexpr uint32_t OFF_ST2 = OFF_T0 + 2048;
constexpr uint32_t OFF_GB = OFF_T0 + 6144;
constexpr uint32_t OFF_WIN = 0;
constexpr uint32_t OFF_AUXR = 100352;
constexpr uint32_t OFF_AUXS = OFF_STG;

constexpr unsigned SPIN_LIMIT = 1u << 22;

__device__ uint32_t g_epoch[NCTA];
__device__ uint2 g_st1[SEQ];
__device__ uint2 g_modw[6 * DM];
__device__ uint4 g_wp[16 * 7 * 896];
__device__ float2 g_csb[FF];
__device__ uint4 g_x1[16 * 7 * 1024];
__device__ uint4 g_st3[16 * 8 * 128];
__device__ uint4 g_z2[8 * 32 * 896];
__device__ uint4 g_gt[16 * 8 * 1792];
__device__ uint32_t g_cnt_x1[7 * 32];
__device__ uint32_t g_flag_wp[16 * 8];
__device__ uint32_t g_flag_z2[8 * 32 * 8];
__device__ uint32_t g_flag_gt[16 * 8 * 2 * 8];
#define TS(n) do {} while (0)

struct Params {
  const __nv_bfloat16 *x, *a_re, *a_im, *b_re, *b_im, *c_re, *c_im, *log_dt, *dskip, *w_in, *w_sp, *b_sp, *w_out, *cvec, *w_mod;
  __nv_bfloat16* out;
};

__device__ __forceinline__ uint32_t s2u(const void* p) { return (uint32_t)__cvta_generic_to_shared(p); }
__device__ __forceinline__ void mbar_init(uint32_t b, uint32_t c) { asm volatile("mbarrier.init.shared::cta.b64 [%0], %1;" ::"r"(b), "r"(c)); }
__device__ __forceinline__ void mbar_expect(uint32_t b, uint32_t n) { asm volatile("mbarrier.arrive.expect_tx.shared::cta.b64 _, [%0], %1;" ::"r"(b), "r"(n) : "memory"); }
__device__ __forceinline__ void mbar_wait(uint32_t b, uint32_t ph) {
  asm volatile(
      "{.reg .pred p; .reg .u32 c; mov.u32 c, 0;\n"
      "LW: mbarrier.try_wait.parity.shared::cta.b64 p, [%0], %1; @p bra LD;\n"
      "add.u32 c, c, 1; setp.lt.u32 p, c, 4194304; @p bra LW;\n"
      "LD: }" ::"r"(b), "r"(ph) : "memory");
}
__device__ __forceinline__ void mbar_arrive(uint32_t b) { asm volatile("mbarrier.arrive.shared::cta.b64 _, [%0];" ::"r"(b) : "memory"); }
__device__ __forceinline__ void mbar_arrive_cluster(uint32_t b, uint32_t cta) {
  asm volatile("{.reg .b32 r; mapa.shared::cluster.u32 r, %0, %1; mbarrier.arrive.shared::cluster.b64 _, [r];}" ::"r"(b), "r"(cta) : "memory");
}
__device__ __forceinline__ bool elect() { uint32_t e; asm volatile("{.reg .pred p; elect.sync _|p, 0xffffffff; selp.u32 %0,1,0,p;}" : "=r"(e)); return e != 0; }
__device__ __forceinline__ void bar_sync(int id, int n) { asm volatile("bar.sync %0, %1;" ::"r"(id), "r"(n) : "memory"); }
__device__ __forceinline__ void bar_arrive(int id, int n) { asm volatile("bar.arrive %0, %1;" ::"r"(id), "r"(n) : "memory"); }
__device__ __forceinline__ void fence_async_smem() { asm volatile("fence.proxy.async.shared::cta;" ::: "memory"); }
__device__ __forceinline__ void fence_async_all() { asm volatile("fence.proxy.async;" ::: "memory"); }
__device__ __forceinline__ void fence_gpu() { asm volatile("fence.acq_rel.gpu;" ::: "memory"); }
__device__ __forceinline__ void wg_fence() { asm volatile("wgmma.fence.sync.aligned;" ::: "memory"); }
__device__ __forceinline__ void wg_commit() { asm volatile("wgmma.commit_group.sync.aligned;" ::: "memory"); }
template <int N> __device__ __forceinline__ void wg_wait() { asm volatile("wgmma.wait_group.sync.aligned %0;" ::"n"(N) : "memory"); }

__device__ __forceinline__ uint32_t ld_acq(const uint32_t* p) { uint32_t v; asm volatile("ld.acquire.gpu.global.u32 %0, [%1];" : "=r"(v) : "l"(p) : "memory"); return v; }
__device__ __forceinline__ void st_rel(uint32_t* p, uint32_t v) { asm volatile("st.release.gpu.global.u32 [%0], %1;" ::"l"(p), "r"(v) : "memory"); }
__device__ __forceinline__ void red_rel(uint32_t* p, uint32_t v) { asm volatile("red.release.gpu.global.add.u32 [%0], %1;" ::"l"(p), "r"(v) : "memory"); }
__device__ __forceinline__ uint2 ld_rlx2(const uint2* p) { uint2 v; asm volatile("ld.relaxed.gpu.global.v2.u32 {%0,%1}, [%2];" : "=r"(v.x), "=r"(v.y) : "l"(p) : "memory"); return v; }
__device__ __forceinline__ uint4 ld_rlx4(const void* p) { uint4 v; asm volatile("ld.relaxed.gpu.global.v4.u32 {%0,%1,%2,%3}, [%4];" : "=r"(v.x), "=r"(v.y), "=r"(v.z), "=r"(v.w) : "l"(p) : "memory"); return v; }
__device__ __forceinline__ void st_rlx2(uint2* p, uint32_t a, uint32_t b) { asm volatile("st.relaxed.gpu.global.v2.u32 [%0], {%1,%2};" ::"l"(p), "r"(a), "r"(b) : "memory"); }
__device__ __forceinline__ void st_rlx4(uint4* p, uint32_t a, uint32_t b, uint32_t c, uint32_t d) { asm volatile("st.relaxed.gpu.global.v4.u32 [%0], {%1,%2,%3,%4};" ::"l"(p), "r"(a), "r"(b), "r"(c), "r"(d) : "memory"); }
__device__ __forceinline__ void wait_flag(const uint32_t* p, uint32_t target) {
  unsigned it = 0;
  while ((int)(ld_acq(p) - target) < 0 && ++it < SPIN_LIMIT) {}
}
__device__ __forceinline__ float wait_modw(const uint2* p, uint32_t ep) {
  unsigned it = 0;
  uint2 v = ld_rlx2(p);
  while (v.y != ep && ++it < SPIN_LIMIT) v = ld_rlx2(p);
  return __uint_as_float(v.x);
}

__device__ __forceinline__ void bulk_g2s(uint32_t dst, const void* src, uint32_t bytes, uint32_t bar) {
  asm volatile("cp.async.bulk.shared::cluster.global.mbarrier::complete_tx::bytes [%0], [%1], %2, [%3];" ::"r"(dst), "l"(src), "r"(bytes), "r"(bar) : "memory");
}
__device__ __forceinline__ void bulk_g2s_mc(uint32_t dst, const void* src, uint32_t bytes, uint32_t bar) {
  asm volatile("cp.async.bulk.shared::cluster.global.mbarrier::complete_tx::bytes.multicast::cluster [%0], [%1], %2, [%3], %4;" ::"r"(dst), "l"(src), "r"(bytes), "r"(bar), "h"((uint16_t)3) : "memory");
}
__device__ __forceinline__ void tma2d(uint32_t dst, const CUtensorMap* tm, int c0, int c1, uint32_t bar) {
  asm volatile("cp.async.bulk.tensor.2d.shared::cluster.global.mbarrier::complete_tx::bytes [%0], [%1, {%3, %4}], [%2];" ::"r"(dst), "l"(tm), "r"(bar), "r"(c0), "r"(c1) : "memory");
}
__device__ __forceinline__ void tma2d_mc(uint32_t dst, const CUtensorMap* tm, int c0, int c1, uint32_t bar) {
  asm volatile("cp.async.bulk.tensor.2d.shared::cluster.global.mbarrier::complete_tx::bytes.multicast::cluster [%0], [%1, {%3, %4}], [%2], %5;" ::"r"(dst), "l"(tm), "r"(bar), "r"(c0), "r"(c1), "h"((uint16_t)3) : "memory");
}
__device__ __forceinline__ void bulk_s2g(void* dst, uint32_t src, uint32_t bytes) {
  asm volatile("cp.async.bulk.global.shared::cta.bulk_group [%0], [%1], %2;" ::"l"(dst), "r"(src), "r"(bytes) : "memory");
  asm volatile("cp.async.bulk.commit_group;" ::: "memory");
  asm volatile("cp.async.bulk.wait_group 0;" ::: "memory");
}
__device__ __forceinline__ void prefetch_l2(const void* p, uint32_t bytes) { asm volatile("cp.async.bulk.prefetch.L2.global [%0], %1;" ::"l"(p), "r"(bytes) : "memory"); }

__device__ __forceinline__ uint32_t lds32(uint32_t a) { uint32_t v; asm volatile("ld.shared.u32 %0, [%1];" : "=r"(v) : "r"(a)); return v; }
__device__ __forceinline__ uint32_t lds16(uint32_t a) { uint16_t v; asm volatile("ld.shared.u16 %0, [%1];" : "=h"(v) : "r"(a)); return v; }
__device__ __forceinline__ float ldsf(uint32_t a) { float v; asm volatile("ld.shared.f32 %0, [%1];" : "=f"(v) : "r"(a)); return v; }
__device__ __forceinline__ float2 lds2f(uint32_t a) { float2 v; asm volatile("ld.shared.v2.f32 {%0,%1}, [%2];" : "=f"(v.x), "=f"(v.y) : "r"(a)); return v; }
__device__ __forceinline__ float4 lds4f(uint32_t a) { float4 v; asm volatile("ld.shared.v4.f32 {%0,%1,%2,%3}, [%4];" : "=f"(v.x), "=f"(v.y), "=f"(v.z), "=f"(v.w) : "r"(a)); return v; }
__device__ __forceinline__ uint4 lds128(uint32_t a) { uint4 v; asm volatile("ld.shared.v4.u32 {%0,%1,%2,%3}, [%4];" : "=r"(v.x), "=r"(v.y), "=r"(v.z), "=r"(v.w) : "r"(a)); return v; }
__device__ __forceinline__ void sts32(uint32_t a, uint32_t v) { asm volatile("st.shared.u32 [%0], %1;" ::"r"(a), "r"(v) : "memory"); }
__device__ __forceinline__ void stsf(uint32_t a, float v) { asm volatile("st.shared.f32 [%0], %1;" ::"r"(a), "f"(v) : "memory"); }
__device__ __forceinline__ void sts2f(uint32_t a, float x, float y) { asm volatile("st.shared.v2.f32 [%0], {%1,%2};" ::"r"(a), "f"(x), "f"(y) : "memory"); }
__device__ __forceinline__ void sts4f(uint32_t a, float x, float y, float z, float w) { asm volatile("st.shared.v4.f32 [%0], {%1,%2,%3,%4};" ::"r"(a), "f"(x), "f"(y), "f"(z), "f"(w) : "memory"); }
__device__ __forceinline__ void sts128(uint32_t a, uint32_t x, uint32_t y, uint32_t z, uint32_t w) { asm volatile("st.shared.v4.u32 [%0], {%1,%2,%3,%4};" ::"r"(a), "r"(x), "r"(y), "r"(z), "r"(w) : "memory"); }
__device__ __forceinline__ void ldsm4(uint32_t a, uint32_t& r0, uint32_t& r1, uint32_t& r2, uint32_t& r3) { asm volatile("ldmatrix.sync.aligned.m8n8.x4.shared.b16 {%0,%1,%2,%3}, [%4];" : "=r"(r0), "=r"(r1), "=r"(r2), "=r"(r3) : "r"(a) : "memory"); }
__device__ __forceinline__ void ldsm2(uint32_t a, uint32_t& r0, uint32_t& r1) { asm volatile("ldmatrix.sync.aligned.m8n8.x2.shared.b16 {%0,%1}, [%2];" : "=r"(r0), "=r"(r1) : "r"(a) : "memory"); }
__device__ __forceinline__ void ldsm4t(uint32_t a, uint32_t& r0, uint32_t& r1, uint32_t& r2, uint32_t& r3) { asm volatile("ldmatrix.sync.aligned.m8n8.x4.trans.shared.b16 {%0,%1,%2,%3}, [%4];" : "=r"(r0), "=r"(r1), "=r"(r2), "=r"(r3) : "r"(a) : "memory"); }
__device__ __forceinline__ void stsm4(uint32_t a, uint32_t r0, uint32_t r1, uint32_t r2, uint32_t r3) { asm volatile("stmatrix.sync.aligned.m8n8.x4.shared.b16 [%0], {%1,%2,%3,%4};" ::"r"(a), "r"(r0), "r"(r1), "r"(r2), "r"(r3) : "memory"); }
__device__ __forceinline__ void stsm2(uint32_t a, uint32_t r0, uint32_t r1) { asm volatile("stmatrix.sync.aligned.m8n8.x2.shared.b16 [%0], {%1,%2};" ::"r"(a), "r"(r0), "r"(r1) : "memory"); }
__device__ __forceinline__ void stsm4t(uint32_t a, uint32_t r0, uint32_t r1, uint32_t r2, uint32_t r3) { asm volatile("stmatrix.sync.aligned.m8n8.x4.trans.shared.b16 [%0], {%1,%2,%3,%4};" ::"r"(a), "r"(r0), "r"(r1), "r"(r2), "r"(r3) : "memory"); }
__device__ __forceinline__ void mma16816(float* d, uint32_t a0, uint32_t a1, uint32_t a2, uint32_t a3, uint32_t b0, uint32_t b1) {
  asm volatile("mma.sync.aligned.m16n8k16.row.col.f32.bf16.bf16.f32 {%0,%1,%2,%3}, {%4,%5,%6,%7}, {%8,%9}, {%0,%1,%2,%3};"
               : "+f"(d[0]), "+f"(d[1]), "+f"(d[2]), "+f"(d[3]) : "r"(a0), "r"(a1), "r"(a2), "r"(a3), "r"(b0), "r"(b1));
}

__device__ __forceinline__ uint32_t pack_bf16(float lo, float hi) { uint32_t r; asm("cvt.rn.bf16x2.f32 %0, %1, %2;" : "=r"(r) : "f"(hi), "f"(lo)); return r; }
__device__ __forceinline__ float bf_lo(uint32_t v) { return __uint_as_float(v << 16); }
__device__ __forceinline__ float bf_hi(uint32_t v) { return __uint_as_float(v & 0xffff0000u); }
__device__ __forceinline__ float round_bf16(float x) { return bf_lo(pack_bf16(x, 0.f)); }
__device__ __forceinline__ uint32_t bf2_mul(uint32_t a, uint32_t b) { uint32_t r; asm("mul.rn.bf16x2 %0, %1, %2;" : "=r"(r) : "r"(a), "r"(b)); return r; }
__device__ __forceinline__ uint32_t bf2_add(uint32_t a, uint32_t b) { uint32_t r; asm("add.rn.bf16x2 %0, %1, %2;" : "=r"(r) : "r"(a), "r"(b)); return r; }
__device__ __forceinline__ uint32_t bf2_sub(uint32_t a, uint32_t b) { uint32_t r; asm("sub.rn.bf16x2 %0, %1, %2;" : "=r"(r) : "r"(a), "r"(b)); return r; }
__device__ __forceinline__ uint32_t dup_bf16(float v) { return pack_bf16(v, v); }
__device__ __forceinline__ float ldg_bf16(const __nv_bfloat16* p) { return __uint_as_float((uint32_t)__ldg(reinterpret_cast<const unsigned short*>(p)) << 16); }
__device__ __forceinline__ float gelu_tanh(float x) {
  float u = x * fmaf(0.0356774081f, x * x, 0.7978845608f);
  float t; asm("tanh.approx.f32 %0, %1;" : "=f"(t) : "f"(u));
  float hx = 0.5f * x;
  return fmaf(hx, t, hx);
}

__device__ __forceinline__ uint64_t desc_sw128(uint32_t addr) { return (uint64_t)((addr & 0x3FFFF) >> 4) | ((uint64_t)1 << 16) | ((uint64_t)64 << 32) | ((uint64_t)1 << 62); }
__device__ __forceinline__ uint64_t desc_nosw(uint32_t addr, uint32_t lbo, uint32_t sbo) { return (uint64_t)((addr & 0x3FFFF) >> 4) | ((uint64_t)(lbo >> 4) << 16) | ((uint64_t)(sbo >> 4) << 32); }

__device__ __forceinline__ void wgmma_n112_tA(float* d, uint64_t da, uint64_t db, int sd) {
  asm volatile("{.reg .pred p; setp.ne.b32 p, %58, 0;\n"
    "wgmma.mma_async.sync.aligned.m64n112k16.f32.bf16.bf16 {%0,%1,%2,%3,%4,%5,%6,%7,%8,%9,%10,%11,%12,%13,%14,%15,%16,%17,%18,%19,%20,%21,%22,%23,%24,%25,%26,%27,%28,%29,%30,%31,%32,%33,%34,%35,%36,%37,%38,%39,%40,%41,%42,%43,%44,%45,%46,%47,%48,%49,%50,%51,%52,%53,%54,%55}, %56, %57, p, 1, 1, 1, 0;}"
    : "+f"(d[0]),"+f"(d[1]),"+f"(d[2]),"+f"(d[3]),"+f"(d[4]),"+f"(d[5]),"+f"(d[6]),"+f"(d[7]),"+f"(d[8]),"+f"(d[9]),"+f"(d[10]),"+f"(d[11]),"+f"(d[12]),"+f"(d[13]),"+f"(d[14]),"+f"(d[15]),"+f"(d[16]),"+f"(d[17]),"+f"(d[18]),"+f"(d[19]),"+f"(d[20]),"+f"(d[21]),"+f"(d[22]),"+f"(d[23]),"+f"(d[24]),"+f"(d[25]),"+f"(d[26]),"+f"(d[27]),"+f"(d[28]),"+f"(d[29]),"+f"(d[30]),"+f"(d[31]),"+f"(d[32]),"+f"(d[33]),"+f"(d[34]),"+f"(d[35]),"+f"(d[36]),"+f"(d[37]),"+f"(d[38]),"+f"(d[39]),"+f"(d[40]),"+f"(d[41]),"+f"(d[42]),"+f"(d[43]),"+f"(d[44]),"+f"(d[45]),"+f"(d[46]),"+f"(d[47]),"+f"(d[48]),"+f"(d[49]),"+f"(d[50]),"+f"(d[51]),"+f"(d[52]),"+f"(d[53]),"+f"(d[54]),"+f"(d[55])
    : "l"(da), "l"(db), "r"(sd));
}
__device__ __forceinline__ void wgmma_n112(float* d, uint64_t da, uint64_t db, int sd) {
  asm volatile("{.reg .pred p; setp.ne.b32 p, %58, 0;\n"
    "wgmma.mma_async.sync.aligned.m64n112k16.f32.bf16.bf16 {%0,%1,%2,%3,%4,%5,%6,%7,%8,%9,%10,%11,%12,%13,%14,%15,%16,%17,%18,%19,%20,%21,%22,%23,%24,%25,%26,%27,%28,%29,%30,%31,%32,%33,%34,%35,%36,%37,%38,%39,%40,%41,%42,%43,%44,%45,%46,%47,%48,%49,%50,%51,%52,%53,%54,%55}, %56, %57, p, 1, 1, 0, 0;}"
    : "+f"(d[0]),"+f"(d[1]),"+f"(d[2]),"+f"(d[3]),"+f"(d[4]),"+f"(d[5]),"+f"(d[6]),"+f"(d[7]),"+f"(d[8]),"+f"(d[9]),"+f"(d[10]),"+f"(d[11]),"+f"(d[12]),"+f"(d[13]),"+f"(d[14]),"+f"(d[15]),"+f"(d[16]),"+f"(d[17]),"+f"(d[18]),"+f"(d[19]),"+f"(d[20]),"+f"(d[21]),"+f"(d[22]),"+f"(d[23]),"+f"(d[24]),"+f"(d[25]),"+f"(d[26]),"+f"(d[27]),"+f"(d[28]),"+f"(d[29]),"+f"(d[30]),"+f"(d[31]),"+f"(d[32]),"+f"(d[33]),"+f"(d[34]),"+f"(d[35]),"+f"(d[36]),"+f"(d[37]),"+f"(d[38]),"+f"(d[39]),"+f"(d[40]),"+f"(d[41]),"+f"(d[42]),"+f"(d[43]),"+f"(d[44]),"+f"(d[45]),"+f"(d[46]),"+f"(d[47]),"+f"(d[48]),"+f"(d[49]),"+f"(d[50]),"+f"(d[51]),"+f"(d[52]),"+f"(d[53]),"+f"(d[54]),"+f"(d[55])
    : "l"(da), "l"(db), "r"(sd));
}
__device__ __forceinline__ void wgmma_n56_tB(float* d, uint64_t da, uint64_t db, int sd) {
  asm volatile("{.reg .pred p; setp.ne.b32 p, %30, 0;\n"
    "wgmma.mma_async.sync.aligned.m64n56k16.f32.bf16.bf16 {%0,%1,%2,%3,%4,%5,%6,%7,%8,%9,%10,%11,%12,%13,%14,%15,%16,%17,%18,%19,%20,%21,%22,%23,%24,%25,%26,%27}, %28, %29, p, 1, 1, 0, 1;}"
    : "+f"(d[0]),"+f"(d[1]),"+f"(d[2]),"+f"(d[3]),"+f"(d[4]),"+f"(d[5]),"+f"(d[6]),"+f"(d[7]),"+f"(d[8]),"+f"(d[9]),"+f"(d[10]),"+f"(d[11]),"+f"(d[12]),"+f"(d[13]),"+f"(d[14]),"+f"(d[15]),"+f"(d[16]),"+f"(d[17]),"+f"(d[18]),"+f"(d[19]),"+f"(d[20]),"+f"(d[21]),"+f"(d[22]),"+f"(d[23]),"+f"(d[24]),"+f"(d[25]),"+f"(d[26]),"+f"(d[27])
    : "l"(da), "l"(db), "r"(sd));
}
__device__ __forceinline__ void wgmma_rs128(float* d, uint32_t a0, uint32_t a1, uint32_t a2, uint32_t a3, uint64_t db, int sd) {
  asm volatile("{.reg .pred p; setp.ne.b32 p, %69, 0;\n"
    "wgmma.mma_async.sync.aligned.m64n128k16.f32.bf16.bf16 {%0,%1,%2,%3,%4,%5,%6,%7,%8,%9,%10,%11,%12,%13,%14,%15,%16,%17,%18,%19,%20,%21,%22,%23,%24,%25,%26,%27,%28,%29,%30,%31,%32,%33,%34,%35,%36,%37,%38,%39,%40,%41,%42,%43,%44,%45,%46,%47,%48,%49,%50,%51,%52,%53,%54,%55,%56,%57,%58,%59,%60,%61,%62,%63}, {%64,%65,%66,%67}, %68, p, 1, 1, 0;}"
    : "+f"(d[0]),"+f"(d[1]),"+f"(d[2]),"+f"(d[3]),"+f"(d[4]),"+f"(d[5]),"+f"(d[6]),"+f"(d[7]),"+f"(d[8]),"+f"(d[9]),"+f"(d[10]),"+f"(d[11]),"+f"(d[12]),"+f"(d[13]),"+f"(d[14]),"+f"(d[15]),"+f"(d[16]),"+f"(d[17]),"+f"(d[18]),"+f"(d[19]),"+f"(d[20]),"+f"(d[21]),"+f"(d[22]),"+f"(d[23]),"+f"(d[24]),"+f"(d[25]),"+f"(d[26]),"+f"(d[27]),"+f"(d[28]),"+f"(d[29]),"+f"(d[30]),"+f"(d[31]),"+f"(d[32]),"+f"(d[33]),"+f"(d[34]),"+f"(d[35]),"+f"(d[36]),"+f"(d[37]),"+f"(d[38]),"+f"(d[39]),"+f"(d[40]),"+f"(d[41]),"+f"(d[42]),"+f"(d[43]),"+f"(d[44]),"+f"(d[45]),"+f"(d[46]),"+f"(d[47]),"+f"(d[48]),"+f"(d[49]),"+f"(d[50]),"+f"(d[51]),"+f"(d[52]),"+f"(d[53]),"+f"(d[54]),"+f"(d[55]),"+f"(d[56]),"+f"(d[57]),"+f"(d[58]),"+f"(d[59]),"+f"(d[60]),"+f"(d[61]),"+f"(d[62]),"+f"(d[63])
    : "r"(a0), "r"(a1), "r"(a2), "r"(a3), "l"(db), "r"(sd));
}
__device__ __forceinline__ void wgmma_rs96(float* d, uint32_t a0, uint32_t a1, uint32_t a2, uint32_t a3, uint64_t db, int sd) {
  asm volatile("{.reg .pred p; setp.ne.b32 p, %53, 0;\n"
    "wgmma.mma_async.sync.aligned.m64n96k16.f32.bf16.bf16 {%0,%1,%2,%3,%4,%5,%6,%7,%8,%9,%10,%11,%12,%13,%14,%15,%16,%17,%18,%19,%20,%21,%22,%23,%24,%25,%26,%27,%28,%29,%30,%31,%32,%33,%34,%35,%36,%37,%38,%39,%40,%41,%42,%43,%44,%45,%46,%47}, {%48,%49,%50,%51}, %52, p, 1, 1, 0;}"
    : "+f"(d[0]),"+f"(d[1]),"+f"(d[2]),"+f"(d[3]),"+f"(d[4]),"+f"(d[5]),"+f"(d[6]),"+f"(d[7]),"+f"(d[8]),"+f"(d[9]),"+f"(d[10]),"+f"(d[11]),"+f"(d[12]),"+f"(d[13]),"+f"(d[14]),"+f"(d[15]),"+f"(d[16]),"+f"(d[17]),"+f"(d[18]),"+f"(d[19]),"+f"(d[20]),"+f"(d[21]),"+f"(d[22]),"+f"(d[23]),"+f"(d[24]),"+f"(d[25]),"+f"(d[26]),"+f"(d[27]),"+f"(d[28]),"+f"(d[29]),"+f"(d[30]),"+f"(d[31]),"+f"(d[32]),"+f"(d[33]),"+f"(d[34]),"+f"(d[35]),"+f"(d[36]),"+f"(d[37]),"+f"(d[38]),"+f"(d[39]),"+f"(d[40]),"+f"(d[41]),"+f"(d[42]),"+f"(d[43]),"+f"(d[44]),"+f"(d[45]),"+f"(d[46]),"+f"(d[47])
    : "r"(a0), "r"(a1), "r"(a2), "r"(a3), "l"(db), "r"(sd));
}
__device__ __forceinline__ void wgmma_rs64(float* d, uint32_t a0, uint32_t a1, uint32_t a2, uint32_t a3, uint64_t db, int sd) {
  asm volatile("{.reg .pred p; setp.ne.b32 p, %37, 0;\n"
    "wgmma.mma_async.sync.aligned.m64n64k16.f32.bf16.bf16 {%0,%1,%2,%3,%4,%5,%6,%7,%8,%9,%10,%11,%12,%13,%14,%15,%16,%17,%18,%19,%20,%21,%22,%23,%24,%25,%26,%27,%28,%29,%30,%31}, {%32,%33,%34,%35}, %36, p, 1, 1, 0;}"
    : "+f"(d[0]),"+f"(d[1]),"+f"(d[2]),"+f"(d[3]),"+f"(d[4]),"+f"(d[5]),"+f"(d[6]),"+f"(d[7]),"+f"(d[8]),"+f"(d[9]),"+f"(d[10]),"+f"(d[11]),"+f"(d[12]),"+f"(d[13]),"+f"(d[14]),"+f"(d[15]),"+f"(d[16]),"+f"(d[17]),"+f"(d[18]),"+f"(d[19]),"+f"(d[20]),"+f"(d[21]),"+f"(d[22]),"+f"(d[23]),"+f"(d[24]),"+f"(d[25]),"+f"(d[26]),"+f"(d[27]),"+f"(d[28]),"+f"(d[29]),"+f"(d[30]),"+f"(d[31])
    : "r"(a0), "r"(a1), "r"(a2), "r"(a3), "l"(db), "r"(sd));
}
__device__ __forceinline__ void wgmma_rs32(float* d, uint32_t a0, uint32_t a1, uint32_t a2, uint32_t a3, uint64_t db, int sd) {
  asm volatile("{.reg .pred p; setp.ne.b32 p, %21, 0;\n"
    "wgmma.mma_async.sync.aligned.m64n32k16.f32.bf16.bf16 {%0,%1,%2,%3,%4,%5,%6,%7,%8,%9,%10,%11,%12,%13,%14,%15}, {%16,%17,%18,%19}, %20, p, 1, 1, 0;}"
    : "+f"(d[0]),"+f"(d[1]),"+f"(d[2]),"+f"(d[3]),"+f"(d[4]),"+f"(d[5]),"+f"(d[6]),"+f"(d[7]),"+f"(d[8]),"+f"(d[9]),"+f"(d[10]),"+f"(d[11]),"+f"(d[12]),"+f"(d[13]),"+f"(d[14]),"+f"(d[15])
    : "r"(a0), "r"(a1), "r"(a2), "r"(a3), "l"(db), "r"(sd));
}

enum { BAR_WG0 = 1, BAR_WG1 = 2, BAR_WG2 = 3, BAR_CONS = 4, BAR_K2 = 5, BAR_K3 = 6, BAR_RED0 = 7, BAR_RED1 = 8, BAR_AUX = 9 };

struct Cplx { float r, i; };
__device__ __forceinline__ Cplx cmul(Cplx a, Cplx b) { Cplx o; o.r = fmaf(a.r, b.r, -a.i * b.i); o.i = fmaf(a.r, b.i, a.i * b.r); return o; }
__device__ __forceinline__ Cplx cexp_scaled(float ar2, float air, float s) {
  float m; asm("ex2.approx.ftz.f32 %0, %1;" : "=f"(m) : "f"(ar2 * s));
  float rev = air * s; rev -= rintf(rev);
  float ang = rev * 6.283185307179586f;
  Cplx o; o.r = m * __cosf(ang); o.i = m * __sinf(ang); return o;
}

struct GenParams { uint32_t are, aim, bre, bim, cre, cim; float dt; };
__device__ __forceinline__ GenParams load_gen_params(const Params& p, int d, int tw) {
  GenParams g; size_t o = (size_t)d * NMODE + 2 * tw;
  g.are = __ldg((const uint32_t*)(p.a_re + o)); g.aim = __ldg((const uint32_t*)(p.a_im + o));
  g.bre = __ldg((const uint32_t*)(p.b_re + o)); g.bim = __ldg((const uint32_t*)(p.b_im + o));
  g.cre = __ldg((const uint32_t*)(p.c_re + o)); g.cim = __ldg((const uint32_t*)(p.c_im + o));
  g.dt = ldg_bf16(p.log_dt + d);
  return g;
}

__device__ __forceinline__ void gen_kernel(const GenParams& gp, uint32_t wgbuf, uint32_t ktab, int tw, int barid) {
  const int lane = tw & 31, wp = tw >> 5, g = lane >> 2, c = lane & 3;
  const uint32_t buf = wgbuf + wp * GEN_BYTES;
  const float dt = round_bf16(__expf(gp.dt));
  float acc[2][3][4];
#pragma unroll
  for (int a = 0; a < 2; a++)
#pragma unroll
    for (int b = 0; b < 3; b++)
#pragma unroll
      for (int e = 0; e < 4; e++) acc[a][b][e] = 0.f;
#pragma unroll 1
  for (int rnd = 0; rnd < 2; rnd++) {
    const float are = rnd ? bf_hi(gp.are) : bf_lo(gp.are), aim = rnd ? bf_hi(gp.aim) : bf_lo(gp.aim);
    const float bre = dt * (rnd ? bf_hi(gp.bre) : bf_lo(gp.bre)), bim = dt * (rnd ? bf_hi(gp.bim) : bf_lo(gp.bim));
    const float cre = rnd ? bf_hi(gp.cre) : bf_lo(gp.cre), cim = rnd ? bf_hi(gp.cim) : bf_lo(gp.cim);
    const float ar2 = (dt * are) * 1.4426950408889634f, air = (dt * aim) * 0.15915494309189535f;
    Cplx cf; cf.r = cre * bre - cim * bim; cf.i = cre * bim + cim * bre;
    const Cplx z1 = cexp_scaled(ar2, air, 1.f), z256 = cexp_scaled(ar2, air, 256.f);
    Cplx w = cexp_scaled(ar2, air, 8.f); w.i = -w.i;
    const uint32_t col = buf + lane * 4;
    Cplx w2 = cmul(w, w), e0, e1 = w; e0.r = 1.f; e0.i = 0.f;
#pragma unroll
    for (int j = 0; j < 32; j += 2) {
      sts32(col + j * GEN_PITCH, pack_bf16(e0.r, e0.i));
      sts32(col + (j + 1) * GEN_PITCH, pack_bf16(e1.r, e1.i));
      if (j < 30) { e0 = (j == 0) ? w2 : cmul(e0, w2); e1 = cmul(e1, w2); }
    }
    Cplx xv[8]; xv[0] = cf;
#pragma unroll
    for (int i = 1; i < 8; i++) xv[i] = cmul(xv[i - 1], z1);
#pragma unroll
    for (int i = 0; i < 8; i++) sts32(col + (32 + i) * GEN_PITCH, pack_bf16(xv[i].r, xv[i].i));
    Cplx y0 = cmul(xv[0], z256), y2 = cmul(xv[2], z256), y4 = cmul(xv[4], z256), y6 = cmul(xv[6], z256);
    sts32(col + 40 * GEN_PITCH, pack_bf16(y0.r, y0.i)); sts32(col + 41 * GEN_PITCH, pack_bf16(y2.r, y2.i));
    sts32(col + 42 * GEN_PITCH, pack_bf16(y4.r, y4.i)); sts32(col + 43 * GEN_PITCH, pack_bf16(y6.r, y6.i));
    y0 = cmul(y0, z256); y4 = cmul(y4, z256);
    sts32(col + 44 * GEN_PITCH, pack_bf16(y0.r, y0.i)); sts32(col + 45 * GEN_PITCH, pack_bf16(y4.r, y4.i));
    y0 = cmul(y0, z256); y4 = cmul(y4, z256);
    sts32(col + 46 * GEN_PITCH, pack_bf16(y0.r, y0.i)); sts32(col + 47 * GEN_PITCH, pack_bf16(y4.r, y4.i));
#pragma unroll
    for (int i = 0; i < 5; i++) { y0 = cmul(y0, z256); sts32(col + (48 + i) * GEN_PITCH, pack_bf16(y0.r, y0.i)); }
    __syncwarp();
    const uint32_t aaddr = buf + ((lane & 7) + ((lane >> 3) & 1) * 8) * GEN_PITCH + (lane >> 4) * 16;
    const uint32_t baddr = buf + (32 + (lane & 7) + (lane >> 4) * 8) * GEN_PITCH + ((lane >> 3) & 1) * 16;
    const uint32_t baddr2 = buf + (48 + (lane & 7)) * GEN_PITCH + ((lane >> 3) & 1) * 16;
#pragma unroll
    for (int ks = 0; ks < 4; ks++) {
      uint32_t a0[4], a1[4], b[6];
      ldsm4(aaddr + ks * 32, a0[0], a0[1], a0[2], a0[3]);
      ldsm4(aaddr + 16 * GEN_PITCH + ks * 32, a1[0], a1[1], a1[2], a1[3]);
      ldsm4(baddr + ks * 32, b[0], b[1], b[2], b[3]);
      ldsm2(baddr2 + ks * 32, b[4], b[5]);
#pragma unroll
      for (int nt = 0; nt < 3; nt++) {
        mma16816(acc[0][nt], a0[0], a0[1], a0[2], a0[3], b[2 * nt], b[2 * nt + 1]);
        mma16816(acc[1][nt], a1[0], a1[1], a1[2], a1[3], b[2 * nt], b[2 * nt + 1]);
      }
    }
    __syncwarp();
  }
#pragma unroll
  for (int u = 0; u < 6; u++)
#pragma unroll
    for (int e = 0; e < 4; e++) stsf(buf + ((u * 4 + e) * 32 + lane) * 4, acc[u / 3][u % 3][e]);
  bar_sync(barid, 128);
  const uint32_t kd = wgbuf + 4096;
#pragma unroll
  for (int u = 0; u < 6; u++) {
    const uint32_t o = wgbuf + ((u * 4 + wp) * 32 + lane) * 4;
    const float s = (ldsf(o) + ldsf(o + GEN_BYTES)) + (ldsf(o + 2 * GEN_BYTES) + ldsf(o + 3 * GEN_BYTES));
    const int j = 16 * (u / 3) + g + 8 * (wp >> 1), i = 8 * (u % 3) + 2 * c + (wp & 1);
    int hi;
    if (u % 3 == 0) hi = i;
    else if (u % 3 == 1) hi = (i < 12) ? 256 + 2 * (i - 8) : 512 + 256 * ((i - 12) >> 1) + 4 * ((i - 12) & 1);
    else hi = 1024 + 256 * (i - 16);
    const int v = hi + 8 * j;
    const int idx = v < 128 ? v : (int)(__float_as_uint((float)v) >> 16) - 0x4300 + 128;
    if (v <= 2048) stsf(kd + idx * 4, s);
  }
  bar_sync(barid, 128);
  {
    float kv[17];
#pragma unroll
    for (int e = 0; e < 17; e++) {
      const int l = 16 * tw - 1 + e;
      const int idx = l < 128 ? l : (int)(pack_bf16((float)l, 0.f) & 0xffffu) - 0x4300 + 128;
      kv[e] = (l >= 0) ? ldsf(kd + max(idx, 0) * 4) : 0.f;
    }
    uint32_t pe[8], po[8];
#pragma unroll
    for (int u = 0; u < 8; u++) { pe[u] = pack_bf16(kv[2 * u + 1], kv[2 * u]); po[u] = pack_bf16(kv[2 * u + 2], kv[2 * u + 1]); }
    const uint32_t o = ktab + (8 + 8 * tw) * 4;
    sts128(o, pe[0], pe[1], pe[2], pe[3]); sts128(o + 16, pe[4], pe[5], pe[6], pe[7]);
    sts128(o + KTAB_ODD, po[0], po[1], po[2], po[3]); sts128(o + KTAB_ODD + 16, po[4], po[5], po[6], po[7]);
    if (tw < 4) sts128(ktab + (tw & 1) * 16 + (tw >> 1) * KTAB_ODD, 0, 0, 0, 0);
  }
}

__device__ __forceinline__ void ln1_stats(const uint32_t (&v)[2][7], int row0, int lane, uint32_t ep) {
#pragma unroll
  for (int r = 0; r < 2; r++) {
    float s = 0.f;
#pragma unroll
    for (int k = 0; k < 7; k++) s += bf_lo(v[r][k]) + bf_hi(v[r][k]);
#pragma unroll
    for (int o = 16; o; o >>= 1) s += __shfl_xor_sync(0xffffffffu, s, o);
    const float mean = s * (1.f / DM);
    float q = 0.f;
#pragma unroll
    for (int k = 0; k < 7; k++) { float a = bf_lo(v[r][k]) - mean, b = bf_hi(v[r][k]) - mean; q = fmaf(a, a, fmaf(b, b, q)); }
#pragma unroll
    for (int o = 16; o; o >>= 1) q += __shfl_xor_sync(0xffffffffu, q, o);
    const float sd = sqrtf(round_bf16(round_bf16(q * (1.f / DM)) + 1e-5f));
    if (lane == 0) st_rlx2(&g_st1[row0 + r], pack_bf16(mean, sd), ep);
  }
}

__device__ __forceinline__ void conv_channel(uint32_t sb, int q, int cidx, int tw, int wg, int round, uint32_t dsk2, uint32_t ga2) {
  const int lane = tw & 31, h = tw >> 5, g = lane >> 2, c = lane & 3;
  const uint32_t kt = sb + OFF_KTAB + q * KTAB_CH + (g & 1) * KTAB_ODD + (8 + 64 * h + (g >> 1) - c - 4) * 4;
  const uint32_t hb = sb + OFF_H + q * H_CH;
  const uint64_t db = desc_nosw(hb + 8 * 16, H_HI, 128);
  float acc[64];
  uint32_t wa[17], wb[17];
#pragma unroll
  for (int e = 0; e < 17; e++) wa[e] = lds32(kt + e * 16);
  wg_fence();
#pragma unroll
  for (int s = 0; s < 8; s++) wgmma_rs128(acc, wa[2 * s + 1], wa[2 * s + 2], wa[2 * s], wa[2 * s + 1], db - s, s != 0);
  wg_commit();
#pragma unroll
  for (int e = 0; e < 17; e++) wb[e] = lds32(kt + 1024 + e * 16);
  wg_fence();
#pragma unroll
  for (int s = 0; s < 8; s++) wgmma_rs96(acc + 16, wb[2 * s + 1], wb[2 * s + 2], wb[2 * s], wb[2 * s + 1], db - s, 1);
  wg_commit();
  wg_wait<1>();
#pragma unroll
  for (int e = 0; e < 17; e++) wa[e] = lds32(kt + 2048 + e * 16);
  wg_fence();
#pragma unroll
  for (int s = 0; s < 8; s++) wgmma_rs64(acc + 32, wa[2 * s + 1], wa[2 * s + 2], wa[2 * s], wa[2 * s + 1], db - s, 1);
  wg_commit();
  wg_wait<1>();
#pragma unroll
  for (int e = 0; e < 17; e++) wb[e] = lds32(kt + 3072 + e * 16);
  wg_fence();
#pragma unroll
  for (int s = 0; s < 8; s++) wgmma_rs32(acc + 48, wb[2 * s + 1], wb[2 * s + 2], wb[2 * s], wb[2 * s + 1], db - s, 1);
  wg_commit();
  wg_wait<0>();
  if (wg == 1) bar_sync(BAR_RED1, 256);
  else if (round == 1) bar_sync(BAR_RED0, 256);
  const uint32_t red = sb + OFF_RED + lane * 16;
  const int toff = (h * (33 - h)) >> 1;
#pragma unroll
  for (int nu = 0; nu < 16; nu++)
    if (nu + h <= 15) sts4f(red + (toff + nu) * 512, acc[4 * nu], acc[4 * nu + 1], acc[4 * nu + 2], acc[4 * nu + 3]);
  bar_sync(BAR_WG0 + wg, 128);
  float y[4][4];
#pragma unroll
  for (int ii = 0; ii < 4; ii++) {
    const int I = 4 * h + ii;
    float4 s = lds4f(red + I * 512);
#pragma unroll
    for (int hh = 1; hh < 4; hh++) {
      if (I - hh >= 0) {
        const float4 t = lds4f(red + (((hh * (33 - hh)) >> 1) + I - hh) * 512);
        s.x += t.x; s.y += t.y; s.z += t.z; s.w += t.w;
      }
    }
    y[ii][0] = s.x; y[ii][1] = s.y; y[ii][2] = s.z; y[ii][3] = s.w;
  }
  if (wg == 0) bar_arrive(BAR_RED1, 256);
  else if (round == 0) bar_arrive(BAR_RED0, 256);
  const uint32_t xb = sb + OFF_X + q * 4096;
  const int mrow = (lane & 7) + (lane >> 4) * 8, mhalf = (lane >> 3) & 1;
#pragma unroll
  for (int pp = 0; pp < 2; pp++) {
    const int blk = 32 * h + 16 * pp + mrow;
    uint32_t hv[4], xv[4], o[4];
    ldsm4t(hb + mhalf * H_HI + (8 + blk) * 16, hv[0], hv[1], hv[2], hv[3]);
    const uint32_t xa = xb + mhalf * 2048 + blk * 16;
    ldsm4t(xa, xv[0], xv[1], xv[2], xv[3]);
#pragma unroll
    for (int m = 0; m < 4; m++) {
      const float* yy = &y[2 * pp + (m >> 1)][2 * (m & 1)];
      const uint32_t ya = bf2_add(pack_bf16(yy[0], yy[1]), bf2_mul(hv[m], dsk2));
      o[m] = bf2_add(xv[m], bf2_mul(ga2, ya));
    }
    stsm4t(xa, o[0], o[1], o[2], o[3]);
  }
  __syncwarp();
  const int k = q * NCONV + cidx, kb = k >> 6, kr = k & 63;
#pragma unroll
  for (int u = 0; u < 2; u++) {
    const int ch = 64 * h + 32 * u + lane;
    const uint4 v = lds128(xb + (ch & 1) * 2048 + (ch >> 1) * 16);
    const int t64 = ch >> 3;
    g_x1[((t64 >> 1) * 7 + kb) * 1024 + (t64 & 1) * 512 + kr * 8 + ((ch & 7) ^ (kr & 7))] = v;
  }
  fence_async_all();
  bar_sync(BAR_WG0 + wg, 128);
  if (tw == 0) { fence_gpu(); red_rel(&g_cnt_x1[kb * 32], 1u); }
}

struct ModLoads { uint4 v[13]; };
__device__ __forceinline__ void mod_load(ModLoads& m, const Params& p, int col0, int tid) {
  const int ch = tid % 7, rg = tid / 7;
#pragma unroll
  for (int k = 0; k < 13; k++) {
    const int r = rg + 36 * k;
    m.v[k] = (tid < 252 && r < DM) ? __ldg((const uint4*)(p.w_mod + (size_t)r * (6 * DM) + col0 + ch * 8)) : make_uint4(0, 0, 0, 0);
  }
}
__device__ __forceinline__ void mod_finish(const ModLoads& m, uint32_t sb, int col0, int tid, uint32_t ep) {
  const int ch = tid % 7, rg = tid / 7;
  float a[8];
#pragma unroll
  for (int e = 0; e < 8; e++) a[e] = 0.f;
#pragma unroll
  for (int k = 0; k < 13; k++) {
    const int r = min(rg + 36 * k, DM - 1);
    const float s = ldsf(sb + OFF_AUXS + r * 4);
    a[0] = fmaf(s, bf_lo(m.v[k].x), a[0]); a[1] = fmaf(s, bf_hi(m.v[k].x), a[1]);
    a[2] = fmaf(s, bf_lo(m.v[k].y), a[2]); a[3] = fmaf(s, bf_hi(m.v[k].y), a[3]);
    a[4] = fmaf(s, bf_lo(m.v[k].z), a[4]); a[5] = fmaf(s, bf_hi(m.v[k].z), a[5]);
    a[6] = fmaf(s, bf_lo(m.v[k].w), a[6]); a[7] = fmaf(s, bf_hi(m.v[k].w), a[7]);
  }
  bar_sync(BAR_CONS, 256);
  if (tid < 252) {
    sts4f(sb + OFF_AUXR + (rg * 56 + ch * 8) * 4, a[0], a[1], a[2], a[3]);
    sts4f(sb + OFF_AUXR + (rg * 56 + ch * 8 + 4) * 4, a[4], a[5], a[6], a[7]);
  }
  bar_sync(BAR_CONS, 256);
  if (tid < 224) {
    const int cc = tid >> 2, part = tid & 3;
    float s = 0.f;
#pragma unroll
    for (int k = 0; k < 9; k++) s += ldsf(sb + OFF_AUXR + ((part * 9 + k) * 56 + cc) * 4);
    s += __shfl_xor_sync(0xffffffffu, s, 1);
    s += __shfl_xor_sync(0xffffffffu, s, 2);
    if (part == 0) st_rlx2(&g_modw[col0 + cc], __float_as_uint(round_bf16(s)), ep);
  }
}

__global__ void __cluster_dims__(2, 1, 1) __launch_bounds__(NTHREADS, 1)
fused_block_kernel(const __grid_constant__ CUtensorMap tm_wsp, const __grid_constant__ CUtensorMap tm_wout, const Params p) {
  extern __shared__ __align__(1024) unsigned char smem_raw[];
  const uint32_t sb = s2u(smem_raw);
  const int tid = threadIdx.x, lane = tid & 31;
  const int warp = __shfl_sync(0xffffffffu, tid >> 5, 0);
  const int bid = blockIdx.x;
  const uint32_t rank = bid & 1;
  const int cl = bid >> 1;
  const int ti = cl & 15, tj = (cl >> 4) * 2 + (int)rank;
  const bool is_conv = bid < NCONV;
  const uint32_t fullA = sb + OFF_BAR, emptyA = fullA + 8 * NA, fullB = emptyA + 8 * NA, emptyB = fullB + 8 * NB;
  const uint32_t ep = g_epoch[bid] + 1;
  TS(0);
  if (tid == 0) {
    if (sb & 1023) __trap();
    for (int s = 0; s < NA; s++) { mbar_init(fullA + 8 * s, 1); mbar_init(emptyA + 8 * s, 4); }
    for (int s = 0; s < NB; s++) { mbar_init(fullB + 8 * s, 1); mbar_init(emptyB + 8 * s, 2); }
    asm volatile("fence.mbarrier_init.release.cluster;" ::: "memory");
  }
  asm volatile("barrier.cluster.arrive.relaxed.aligned;" ::: "memory");

  if (warp >= 8) {
    const int tw = tid - 256;
    if (is_conv) {
      const GenParams g2 = load_gen_params(p, 4 * bid + 2, tw), g3 = load_gen_params(p, 4 * bid + 3, tw);
      asm volatile("barrier.cluster.wait.aligned;" ::: "memory");
      gen_kernel(g2, sb + OFF_GEN2, sb + OFF_KTAB + 2 * KTAB_CH, tw, BAR_WG2);
      bar_arrive(BAR_K2, 256);
      if (warp == 10 && elect()) {
#pragma unroll
        for (int u = 0; u < 4; u++) prefetch_l2(p.w_sp + (size_t)bid * 32768 + u * 8192, 16384);
        prefetch_l2(p.w_out + (size_t)bid * 3136, 6272);
      }
      bar_sync(BAR_WG2, 128);
      gen_kernel(g3, sb + OFF_GEN2, sb + OFF_KTAB + 3 * KTAB_CH, tw, BAR_WG2);
      bar_arrive(BAR_K3, 256);
      bar_sync(BAR_WG2, 128);
      TS(16);
    } else {
      asm volatile("barrier.cluster.wait.aligned;" ::: "memory");
      bar_sync(BAR_AUX, 384);
      if (warp == 10 && elect()) {
#pragma unroll
        for (int u = 0; u < 4; u++) prefetch_l2(p.w_sp + (size_t)bid * 32768 + u * 8192, 16384);
        prefetch_l2(p.w_out + (size_t)bid * 3136, 6272);
      }
    }
    if (warp == 8) {
      if (elect()) {
        int slot = 0; uint32_t ph = 0;
        for (int kb = 0; kb < 7; kb++) {
          mbar_wait(emptyA + 8 * kb, 0);
          wait_flag(&g_cnt_x1[kb * 32], ep * 64u);
          fence_async_all();
          mbar_expect(fullA + 8 * kb, 16384);
          bulk_g2s_mc(sb + OFF_A + kb * A_SLOT + rank * 8192, (const char*)g_x1 + (size_t)(ti * 7 + kb) * 16384 + rank * 8192, 8192, fullA + 8 * kb);
        }
        ph = 1;
        for (int kk = 0; kk < 32; kk++) {
          mbar_wait(emptyA + 8 * slot, ph);
          mbar_expect(fullA + 8 * slot, 16384);
          tma2d_mc(sb + OFF_A + slot * A_SLOT + rank * 8192, &tm_wsp, kk * 64, ti * 128 + (int)rank * 64, fullA + 8 * slot);
          if (++slot == NA) { slot = 0; ph ^= 1; }
        }
        for (int jj = 0; jj < 8; jj++) {
          const char* src = (const char*)g_gt + ((size_t)(ti * 8 + jj) * 2 + rank) * 14336;
          mbar_wait(emptyA + 8 * slot, ph);
          wait_flag(&g_flag_gt[((ti * 8 + jj) * 2 + rank) * 8], ep);
          fence_async_all();
          mbar_expect(fullA + 8 * slot, 16384);
          bulk_g2s_mc(sb + OFF_A + slot * A_SLOT + rank * 8192, src, 8192, fullA + 8 * slot);
          if (++slot == NA) { slot = 0; ph ^= 1; }
          mbar_wait(emptyA + 8 * slot, ph);
          mbar_expect(fullA + 8 * slot, 12288);
          bulk_g2s_mc(sb + OFF_A + slot * A_SLOT + rank * 8192, src + 8192, 6144, fullA + 8 * slot);
          if (++slot == NA) { slot = 0; ph ^= 1; }
        }
      }
    } else if (warp == 9) {
      if (elect()) {
        int slot = 0; uint32_t ph = 1;
        for (int b = 0; b < 14; b++) {
          const int blk = (b >= 7 ? 8 : 0) + tj, kb = b >= 7 ? b - 7 : b;
          mbar_wait(emptyB + 8 * slot, ph);
          if (kb == 0) { wait_flag(&g_flag_wp[blk * 8], ep); fence_async_all(); }
          mbar_expect(fullB + 8 * slot, B_SLOT);
          bulk_g2s(sb + OFF_B + slot * B_SLOT, (const char*)g_wp + (size_t)(blk * 7 + kb) * B_SLOT, B_SLOT, fullB + 8 * slot);
          if (++slot == NB) { slot = 0; ph ^= 1; }
        }
        for (int kk = 0; kk < 32; kk++) {
          mbar_wait(emptyB + 8 * slot, ph);
          wait_flag(&g_flag_z2[(tj * 32 + kk) * 8], ep);
          fence_async_all();
          mbar_expect(fullB + 8 * slot, B_SLOT);
          bulk_g2s(sb + OFF_B + slot * B_SLOT, (const char*)g_z2 + (size_t)(tj * 32 + kk) * B_SLOT, B_SLOT, fullB + 8 * slot);
          if (++slot == NB) { slot = 0; ph ^= 1; }
        }
        for (int jj = 0; jj < 8; jj++) {
          mbar_wait(emptyB + 8 * slot, ph);
          mbar_expect(fullB + 8 * slot, B_SLOT);
          tma2d(sb + OFF_B + slot * B_SLOT, &tm_wout, tj * 56, jj * 112, fullB + 8 * slot);
          if (++slot == NB) { slot = 0; ph ^= 1; }
        }
      }
    }
    __syncwarp();
  } else {
    const int wg = warp >> 2, tw = tid & 127, wp = warp & 3, g = lane >> 2, c = lane & 3;
    uint32_t rv[2][7];
    {
      const uint32_t* xr = (const uint32_t*)(p.x + (size_t)(16 * bid + 2 * warp) * DM) + lane;
#pragma unroll
      for (int r = 0; r < 2; r++)
#pragma unroll
        for (int k = 0; k < 7; k++) rv[r][k] = __ldg(xr + r * (DM / 2) + 32 * k);
    }
    if (is_conv) {
      const GenParams gp = load_gen_params(p, 4 * bid + wg, tw);
      uint2 xc[8];
#pragma unroll
      for (int e = 0; e < 8; e++) xc[e] = __ldg((const uint2*)(p.x + (size_t)(8 * tid + e) * DM + 4 * bid));
      const uint2 dsk = __ldg((const uint2*)(p.dskip + 4 * bid));
      ln1_stats(rv, 16 * bid + 2 * warp, lane, ep);
      TS(1 + wg);
      asm volatile("barrier.cluster.wait.aligned;" ::: "memory");
      gen_kernel(gp, sb + OFF_GEN01 + wg * 4 * GEN_BYTES, sb + OFF_KTAB + wg * KTAB_CH, tw, BAR_WG0 + wg);
      if (tid < 64) sts128(sb + OFF_H + (tid >> 4) * H_CH + ((tid >> 3) & 1) * H_HI + (tid & 7) * 16, 0, 0, 0, 0);
      TS(3 + wg);
      {
        uint4 st[4];
        unsigned it = 0;
        bool ok;
        do {
#pragma unroll
          for (int u = 0; u < 4; u++) st[u] = ld_rlx4((const uint4*)&g_st1[8 * tid] + u);
          ok = true;
#pragma unroll
          for (int u = 0; u < 4; u++) ok = ok && st[u].y == ep && st[u].w == ep;
        } while (!ok && ++it < SPIN_LIMIT);
        uint32_t ca1[4], sa2[4];
#pragma unroll
        for (int q = 0; q < 4; q++) {
          sa2[q] = dup_bf16(wait_modw(&g_modw[4 * bid + q], ep));
          ca1[q] = dup_bf16(1.f + wait_modw(&g_modw[DM + 4 * bid + q], ep));
        }
        float n[8][4];
#pragma unroll
        for (int e = 0; e < 8; e++) {
          const uint32_t w = (e & 1) ? st[e >> 1].z : st[e >> 1].x;
          const uint32_t m2 = __byte_perm(w, w, 0x1010);
          const float rs = __frcp_rn(bf_hi(w));
          const uint32_t d01 = bf2_sub(xc[e].x, m2), d23 = bf2_sub(xc[e].y, m2);
          n[e][0] = bf_lo(d01) * rs; n[e][1] = bf_hi(d01) * rs; n[e][2] = bf_lo(d23) * rs; n[e][3] = bf_hi(d23) * rs;
        }
#pragma unroll
        for (int q = 0; q < 4; q++) {
          uint32_t hv[4], xv[4];
#pragma unroll
          for (int u = 0; u < 4; u++) {
            hv[u] = bf2_add(bf2_mul(pack_bf16(n[2 * u][q], n[2 * u + 1][q]), ca1[q]), sa2[q]);
            const uint32_t a = (q < 2) ? xc[2 * u].x : xc[2 * u].y, b = (q < 2) ? xc[2 * u + 1].x : xc[2 * u + 1].y;
            xv[u] = __byte_perm(a, b, (q & 1) ? 0x7632 : 0x5410);
          }
          sts128(sb + OFF_H + q * H_CH + (tid & 1) * H_HI + (8 + (tid >> 1)) * 16, hv[0], hv[1], hv[2], hv[3]);
          sts128(sb + OFF_X + q * 4096 + (tid & 1) * 2048 + (tid >> 1) * 16, xv[0], xv[1], xv[2], xv[3]);
        }
      }
      fence_async_smem();
      bar_sync(BAR_CONS, 256);
      if (tw < 6) mbar_arrive_cluster(emptyA + 8 * (tw >> 1), tw & 1);
      TS(5 + wg);
      const uint32_t dk_a = wg ? __byte_perm(dsk.x, 0, 0x3232) : __byte_perm(dsk.x, 0, 0x1010);
      const uint32_t dk_b = wg ? __byte_perm(dsk.y, 0, 0x3232) : __byte_perm(dsk.y, 0, 0x1010);
      const uint32_t ga_a = dup_bf16(wait_modw(&g_modw[2 * DM + 4 * bid + wg], ep));
      const uint32_t ga_b = dup_bf16(wait_modw(&g_modw[2 * DM + 4 * bid + 2 + wg], ep));
      conv_channel(sb, wg, bid, tw, wg, 0, dk_a, ga_a);
      TS(7 + wg);
      bar_sync(BAR_K2 + wg, 256);
      conv_channel(sb, 2 + wg, bid, tw, wg, 1, dk_b, ga_b);
      bar_sync(BAR_CONS, 256);
      if (tw < 8) mbar_arrive_cluster(emptyA + 8 * (3 + (tw >> 1)), tw & 1);
      TS(9 + wg);
    } else {
      const int a = bid - NCONV;
      const int wcol = (a < 8 ? FH : 0) + 112 * (a & 7);
      for (int u = tid; u < DM * 14; u += 256) {
        const int r = u / 14, cc = u - r * 14;
        asm volatile("cp.async.cg.shared.global [%0], [%1], 16;" ::"r"(sb + OFF_WIN + r * 224 + cc * 16), "l"(p.w_in + (size_t)r * FF + wcol + cc * 8) : "memory");
      }
      asm volatile("cp.async.commit_group;" ::: "memory");
      ModLoads m1, m2;
      const int c1 = 56 * a, c2 = 3 * DM + 56 * a, c3 = (a < 8 ? 2 * DM : 5 * DM) + 56 * (a & 7);
      mod_load(m1, p, c1, tid);
      for (int u = tid; u < DM; u += 256) { const float cv = ldg_bf16(p.cvec + u); stsf(sb + OFF_AUXS + u * 4, round_bf16(cv / (1.f + __expf(-cv)))); }
      mod_load(m2, p, c2, tid);
      ln1_stats(rv, 16 * bid + 2 * warp, lane, ep);
      asm volatile("barrier.cluster.wait.aligned;" ::: "memory");
      bar_sync(BAR_CONS, 256);
      mod_finish(m1, sb, c1, tid, ep);
      TS(1 + wg);
      mod_load(m1, p, c3, tid);
      mod_finish(m2, sb, c2, tid, ep);
      mod_finish(m1, sb, c3, tid, ep);
      TS(3 + wg);
      for (int u = tid; u < 2 * DM; u += 256) {
        const float v = wait_modw(&g_modw[3 * DM + u], ep);
        if (u < DM) stsf(sb + OFF_AUXS + (2 * DM + u) * 4, v); else stsf(sb + OFF_AUXS + u * 4, round_bf16(1.f + v));
      }
      asm volatile("cp.async.wait_group 0;" ::: "memory");
      bar_sync(BAR_CONS, 256);
      if (tid < 224) {
        const int n2 = tid % 56, q = tid / 56;
        float cs0 = 0.f, cs1 = 0.f, bi0 = 0.f, bi1 = 0.f;
#pragma unroll 2
        for (int c8 = 0; c8 < 14; c8++) {
          float w0[8], w1[8];
#pragma unroll
          for (int e = 0; e < 8; e++) {
            const int d = 4 * (8 * c8 + e) + q;
            const uint32_t w = lds32(sb + OFF_WIN + d * 224 + n2 * 4);
            const float s1 = ldsf(sb + OFF_AUXS + (DM + d) * 4), s0 = ldsf(sb + OFF_AUXS + (2 * DM + d) * 4);
            bi0 = fmaf(s0, bf_lo(w), bi0); bi1 = fmaf(s0, bf_hi(w), bi1);
            const uint32_t wpk = pack_bf16(s1 * bf_lo(w), s1 * bf_hi(w));
            w0[e] = bf_lo(wpk); w1[e] = bf_hi(wpk);
            cs0 += w0[e]; cs1 += w1[e];
          }
          const int k = q * NCONV + 8 * c8;
          uint4* dst = &g_wp[(a * 7 + (k >> 6)) * 896 + ((k & 63) >> 3) * 112 + 2 * n2];
          dst[0] = make_uint4(pack_bf16(w0[0], w0[1]), pack_bf16(w0[2], w0[3]), pack_bf16(w0[4], w0[5]), pack_bf16(w0[6], w0[7]));
          dst[1] = make_uint4(pack_bf16(w1[0], w1[1]), pack_bf16(w1[2], w1[3]), pack_bf16(w1[4], w1[5]), pack_bf16(w1[6], w1[7]));
        }
        sts4f(sb + OFF_AUXR + (q * 56 + n2) * 16, cs0, bi0, cs1, bi1);
      }
      bar_sync(BAR_CONS, 256);
      if (tid < 56) {
        float4 s = lds4f(sb + OFF_AUXR + tid * 16);
#pragma unroll
        for (int q = 1; q < 4; q++) { const float4 t = lds4f(sb + OFF_AUXR + (q * 56 + tid) * 16); s.x += t.x; s.y += t.y; s.z += t.z; s.w += t.w; }
        *(float4*)&g_csb[a * 112 + 2 * tid] = s;
      }
      fence_async_all();
      bar_sync(BAR_CONS, 256);
      if (tid == 0) { fence_gpu(); st_rel(&g_flag_wp[a * 8], ep); }
      bar_arrive(BAR_AUX, 384);
      if (tw < 14) mbar_arrive_cluster(emptyA + 8 * (tw >> 1), tw & 1);
      TS(9 + wg);
    }

    float acc2[56], acc1[56];
    float sum[8], sq[8];
#pragma unroll
    for (int e = 0; e < 8; e++) { sum[e] = 0.f; sq[e] = 0.f; }
    int bs = 0; uint32_t bph = 0;
    int prevb = -1;
    const uint32_t stat_off = wg * 8192 + (tw >> 3) * 128 + (((tw & 7) ^ ((tw >> 3) & 7)) * 16);
#pragma unroll 1
    for (int kb = 0; kb < 7; kb++) {
      mbar_wait(fullA + 8 * kb, 0);
      mbar_wait(fullB + 8 * bs, bph);
      const uint64_t da = desc_sw128(sb + OFF_A + kb * A_SLOT + wg * 8192), db = desc_nosw(sb + OFF_B + bs * B_SLOT, 1792, 128);
      wg_fence();
#pragma unroll
      for (int k = 0; k < 4; k++) wgmma_n112_tA(acc2, da + 128 * k, db + 224 * k, (kb | k) != 0);
      wg_commit();
#pragma unroll
      for (int e = 0; e < 4; e++) {
        const uint4 v = lds128(sb + OFF_A + kb * A_SLOT + stat_off + e * 2048);
        const uint32_t w[4] = {v.x, v.y, v.z, v.w};
#pragma unroll
        for (int u = 0; u < 4; u++) {
          const float lo = bf_lo(w[u]), hi = bf_hi(w[u]);
          sum[2 * u] += lo; sq[2 * u] = fmaf(lo, lo, sq[2 * u]);
          sum[2 * u + 1] += hi; sq[2 * u + 1] = fmaf(hi, hi, sq[2 * u + 1]);
        }
      }
      wg_wait<1>();
      if (prevb >= 0 && tw == 0) mbar_arrive(emptyB + 8 * prevb);
      prevb = bs;
      if (++bs == NB) { bs = 0; bph ^= 1; }
    }
    TS(11 + wg);
#pragma unroll 1
    for (int kb = 0; kb < 7; kb++) {
      mbar_wait(fullB + 8 * bs, bph);
      const uint64_t da = desc_sw128(sb + OFF_A + kb * A_SLOT + wg * 8192), db = desc_nosw(sb + OFF_B + bs * B_SLOT, 1792, 128);
      wg_fence();
#pragma unroll
      for (int k = 0; k < 4; k++) wgmma_n112_tA(acc1, da + 128 * k, db + 224 * k, (kb | k) != 0);
      wg_commit();
      wg_wait<1>();
      if (tw == 0) mbar_arrive(emptyB + 8 * prevb);
      prevb = bs;
      if (++bs == NB) { bs = 0; bph ^= 1; }
    }
    uint32_t xres[14];
    {
      const int tl = 16 * wp + g;
#pragma unroll
      for (int n = 0; n < 7; n++) {
#pragma unroll
        for (int hf = 0; hf < 2; hf++) {
          uint32_t v[2];
#pragma unroll
          for (int e = 0; e < 2; e++) {
            const int d = 56 * tj + 8 * n + 2 * c + e;
            const int k = (d & 3) * NCONV + (d >> 2);
            const int t = tl + 8 * hf;
            v[e] = lds16(sb + OFF_A + (k >> 6) * A_SLOT + wg * 8192 + (k & 63) * 128 + (((t >> 3) ^ (k & 7)) * 16) + (t & 7) * 2);
          }
          xres[2 * n + hf] = v[0] | (v[1] << 16);
        }
      }
    }
#pragma unroll
    for (int e = 0; e < 8; e++) {
      sum[e] += __shfl_xor_sync(0xffffffffu, sum[e], 8); sum[e] += __shfl_xor_sync(0xffffffffu, sum[e], 16);
      sq[e] += __shfl_xor_sync(0xffffffffu, sq[e], 8); sq[e] += __shfl_xor_sync(0xffffffffu, sq[e], 16);
    }
    if (lane < 8) {
      const uint32_t o = sb + OFF_ST2 + ((wg * 4 + wp) * 64 + lane * 8) * 8;
      sts4f(o, sum[0], sq[0], sum[1], sq[1]); sts4f(o + 16, sum[2], sq[2], sum[3], sq[3]);
      sts4f(o + 32, sum[4], sq[4], sum[5], sq[5]); sts4f(o + 48, sum[6], sq[6], sum[7], sq[7]);
    }
    if (tid < 224) {
      const int blk = (tid >= 112 ? 8 : 0) + tj;
      wait_flag(&g_flag_wp[blk * 8], ep);
      const float2 v = __ldcg(&g_csb[blk * 112 + (tid >= 112 ? tid - 112 : tid)]);
      sts2f(sb + OFF_CSB + tid * 8, v.x, v.y);
    } else if (tid < 252) {
      const int u = tid - 224;
      const float g0 = wait_modw(&g_modw[5 * DM + 56 * tj + 2 * u], ep), g1 = wait_modw(&g_modw[5 * DM + 56 * tj + 2 * u + 1], ep);
      sts32(sb + OFF_GB + u * 4, pack_bf16(g0, g1));
    }
    wg_wait<0>();
    if (tw == 0) mbar_arrive(emptyB + 8 * prevb);
    bar_sync(BAR_CONS, 256);
    if (tw < 14) mbar_arrive_cluster(emptyA + 8 * (tw >> 1), tw & 1);
    TS(13 + wg);
    float ra[2], rb[2];
#pragma unroll
    for (int hf = 0; hf < 2; hf++) {
      float s = 0.f, q = 0.f;
#pragma unroll
      for (int w = 0; w < 4; w++) { const float2 v = lds2f(sb + OFF_ST2 + ((wg * 4 + w) * 64 + 16 * wp + g + 8 * hf) * 8); s += v.x; q += v.y; }
      const float mean = s * (1.f / DM);
      const float var = fmaxf(q * (1.f / DM) - mean * mean, 0.f);
      ra[hf] = rsqrtf(var + 1e-5f); rb[hf] = -ra[hf] * mean;
    }
    {
      float s0 = 0.f, q0 = 0.f, s1 = 0.f, q1 = 0.f;
#pragma unroll
      for (int n = 0; n < 14; n++) {
        const float4 cb = lds4f(sb + OFF_CSB + (8 * n + 2 * c) * 8);
        float* a = acc2 + 4 * n;
        a[0] = gelu_tanh(fmaf(ra[0], a[0], fmaf(rb[0], cb.x, cb.y))); a[1] = gelu_tanh(fmaf(ra[0], a[1], fmaf(rb[0], cb.z, cb.w)));
        a[2] = gelu_tanh(fmaf(ra[1], a[2], fmaf(rb[1], cb.x, cb.y))); a[3] = gelu_tanh(fmaf(ra[1], a[3], fmaf(rb[1], cb.z, cb.w)));
        s0 += a[0] + a[1]; q0 = fmaf(a[0], a[0], fmaf(a[1], a[1], q0));
        s1 += a[2] + a[3]; q1 = fmaf(a[2], a[2], fmaf(a[3], a[3], q1));
      }
#pragma unroll
      for (int o = 1; o < 4; o <<= 1) {
        s0 += __shfl_xor_sync(0xffffffffu, s0, o); q0 += __shfl_xor_sync(0xffffffffu, q0, o);
        s1 += __shfl_xor_sync(0xffffffffu, s1, o); q1 += __shfl_xor_sync(0xffffffffu, q1, o);
      }
      const int row = 64 * wg + 16 * wp + g;
      if (c < 2) st_rlx4(&g_st3[(ti * 8 + tj) * 128 + row + 8 * c], __float_as_uint(c ? s1 : s0), ep, __float_as_uint(c ? q1 : q0), ep);
#pragma unroll
      for (int n = 0; n < 14; n++) {
        const float4 cb = lds4f(sb + OFF_CSB + (112 + 8 * n + 2 * c) * 8);
        float* a = acc1 + 4 * n;
        a[0] = gelu_tanh(fmaf(ra[0], a[0], fmaf(rb[0], cb.x, cb.y))); a[1] = gelu_tanh(fmaf(ra[0], a[1], fmaf(rb[0], cb.z, cb.w)));
        a[2] = gelu_tanh(fmaf(ra[1], a[2], fmaf(rb[1], cb.x, cb.y))); a[3] = gelu_tanh(fmaf(ra[1], a[3], fmaf(rb[1], cb.z, cb.w)));
      }
      uint4 st[4];
      unsigned it = 0;
      bool ok;
      do {
#pragma unroll
        for (int u = 0; u < 4; u++) st[u] = ld_rlx4(&g_st3[(ti * 8 + c + 4 * (u & 1)) * 128 + row + 8 * (u >> 1)]);
        ok = true;
#pragma unroll
        for (int u = 0; u < 4; u++) ok = ok && st[u].y == ep && st[u].w == ep;
      } while (!ok && ++it < SPIN_LIMIT);
      s0 = __uint_as_float(st[0].x) + __uint_as_float(st[1].x); q0 = __uint_as_float(st[0].z) + __uint_as_float(st[1].z);
      s1 = __uint_as_float(st[2].x) + __uint_as_float(st[3].x); q1 = __uint_as_float(st[2].z) + __uint_as_float(st[3].z);
#pragma unroll
      for (int o = 1; o < 4; o <<= 1) {
        s0 += __shfl_xor_sync(0xffffffffu, s0, o); q0 += __shfl_xor_sync(0xffffffffu, q0, o);
        s1 += __shfl_xor_sync(0xffffffffu, s1, o); q1 += __shfl_xor_sync(0xffffffffu, q1, o);
      }
      const float m0 = s0 * (1.f / FH), m1 = s1 * (1.f / FH);
      const float r0 = rsqrtf(fmaxf(q0 * (1.f / FH) - m0 * m0, 0.f) + 1e-5f), r1 = rsqrtf(fmaxf(q1 * (1.f / FH) - m1 * m1, 0.f) + 1e-5f);
      const float o0 = -m0 * r0, o1 = -m1 * r1;
      const uint32_t sa = sb + OFF_STG + wg * B_SLOT + (2 * wp + ((lane >> 3) & 1)) * 1792 + ((lane & 7) + (lane >> 4) * 8) * 16;
#pragma unroll
      for (int n = 0; n < 14; n += 2) {
        const float* a = acc2 + 4 * n;
        stsm4t(sa + n * 128, pack_bf16(fmaf(a[0], r0, o0), fmaf(a[1], r0, o0)), pack_bf16(fmaf(a[2], r1, o1), fmaf(a[3], r1, o1)),
               pack_bf16(fmaf(a[4], r0, o0), fmaf(a[5], r0, o0)), pack_bf16(fmaf(a[6], r1, o1), fmaf(a[7], r1, o1)));
      }
      fence_async_smem();
      bar_sync(BAR_WG0 + wg, 128);
      if (tw == 0) {
        bulk_s2g((char*)g_z2 + (size_t)(tj * 32 + 2 * ti + wg) * B_SLOT, sb + OFF_STG + wg * B_SLOT, B_SLOT);
        fence_gpu();
        st_rel(&g_flag_z2[(tj * 32 + 2 * ti + wg) * 8], ep);
      }
    }
    uint32_t z1[28];
#pragma unroll
    for (int n = 0; n < 28; n++) z1[n] = pack_bf16(acc1[2 * n], acc1[2 * n + 1]);
    const uint32_t bsp0 = dup_bf16(ldg_bf16(p.b_sp + ti * 128 + 64 * wg + 16 * wp + g)), bsp1 = dup_bf16(ldg_bf16(p.b_sp + ti * 128 + 64 * wg + 16 * wp + g + 8));
    TS(17 + wg);

    int as = 0; uint32_t aph = 1;
    int preva = -1; prevb = -1;
#pragma unroll 1
    for (int kk = 0; kk < 32; kk++) {
      mbar_wait(fullA + 8 * as, aph);
      mbar_wait(fullB + 8 * bs, bph);
      if (kk == 0) TS(19 + wg);
      const uint64_t da = desc_sw128(sb + OFF_A + as * A_SLOT + wg * 8192), db = desc_nosw(sb + OFF_B + bs * B_SLOT, 1792, 128);
      wg_fence();
#pragma unroll
      for (int k = 0; k < 4; k++) wgmma_n112(acc2, da + 2 * k, db + 224 * k, (kk | k) != 0);
      wg_commit();
      wg_wait<1>();
      if (preva >= 0) {
        if (tw < 2) mbar_arrive_cluster(emptyA + 8 * preva, tw);
        else if (tw == 32) mbar_arrive(emptyB + 8 * prevb);
      }
      preva = as; prevb = bs;
      if (++as == NA) { as = 0; aph ^= 1; }
      if (++bs == NB) { bs = 0; bph ^= 1; }
    }
    wg_wait<0>();
    if (tw < 2) mbar_arrive_cluster(emptyA + 8 * preva, tw);
    else if (tw == 32) mbar_arrive(emptyB + 8 * prevb);
    TS(21 + wg);
    {
      const uint32_t sa = sb + OFF_STG + wg * B_SLOT + (lane >> 4) * 1024 + (16 * wp + (lane & 7) + ((lane >> 3) & 1) * 8) * 16;
#pragma unroll
      for (int n = 0; n < 14; n += 2) {
        const float* a = acc2 + 4 * n;
        stsm4(sa + n * 1024, bf2_mul(z1[2 * n], bf2_add(pack_bf16(a[0], a[1]), bsp0)), bf2_mul(z1[2 * n + 1], bf2_add(pack_bf16(a[2], a[3]), bsp1)),
              bf2_mul(z1[2 * n + 2], bf2_add(pack_bf16(a[4], a[5]), bsp0)), bf2_mul(z1[2 * n + 3], bf2_add(pack_bf16(a[6], a[7]), bsp1)));
      }
      fence_async_smem();
      bar_sync(BAR_WG0 + wg, 128);
      if (tw == 0) {
        bulk_s2g((char*)g_gt + ((size_t)(ti * 8 + tj) * 2 + wg) * 14336, sb + OFF_STG + wg * B_SLOT, 14336);
        fence_gpu();
        st_rel(&g_flag_gt[((ti * 8 + tj) * 2 + wg) * 8], ep);
      }
    }
    TS(23 + wg);
    float acc3[28];
    {
      int pa0 = -1, pa1 = -1; prevb = -1;
#pragma unroll 1
      for (int jj = 0; jj < 8; jj++) {
        mbar_wait(fullB + 8 * bs, bph);
        mbar_wait(fullA + 8 * as, aph);
        if (jj == 0) TS(25 + wg);
        const uint64_t db = desc_sw128(sb + OFF_B + bs * B_SLOT);
        const int a0 = as;
        const uint64_t da0 = desc_nosw(sb + OFF_A + as * A_SLOT + wg * 8192, 1024, 128);
        wg_fence();
#pragma unroll
        for (int k = 0; k < 4; k++) wgmma_n56_tB(acc3, da0 + 128 * k, db + 128 * k, (jj | k) != 0);
        if (++as == NA) { as = 0; aph ^= 1; }
        mbar_wait(fullA + 8 * as, aph);
        const uint64_t da1 = desc_nosw(sb + OFF_A + as * A_SLOT + wg * 8192, 1024, 128);
#pragma unroll
        for (int k = 0; k < 3; k++) wgmma_n56_tB(acc3, da1 + 128 * k, db + 128 * (4 + k), 1);
        wg_commit();
        wg_wait<1>();
        if (pa0 >= 0) {
          if (tw < 2) mbar_arrive_cluster(emptyA + 8 * pa0, tw);
          else if (tw < 4) mbar_arrive_cluster(emptyA + 8 * pa1, tw - 2);
          else if (tw == 32) mbar_arrive(emptyB + 8 * prevb);
        }
        pa0 = a0; pa1 = as; prevb = bs;
        if (++as == NA) { as = 0; aph ^= 1; }
        if (++bs == NB) { bs = 0; bph ^= 1; }
      }
      wg_wait<0>();
    }
    TS(27 + wg);
    {
      const uint32_t ob = sb + OFF_STG + warp * 2304;
      uint32_t o[14];
#pragma unroll
      for (int n = 0; n < 7; n++) {
        const uint32_t gb2 = lds32(sb + OFF_GB + (4 * n + c) * 4);
        o[2 * n] = bf2_add(xres[2 * n], bf2_mul(gb2, pack_bf16(acc3[4 * n], acc3[4 * n + 1])));
        o[2 * n + 1] = bf2_add(xres[2 * n + 1], bf2_mul(gb2, pack_bf16(acc3[4 * n + 2], acc3[4 * n + 3])));
      }
      bar_sync(BAR_CONS, 256);
      const uint32_t sa = ob + ((lane & 7) + ((lane >> 3) & 1) * 8) * 144 + (lane >> 4) * 16;
#pragma unroll
      for (int n = 0; n < 6; n += 2) stsm4(sa + n * 16, o[2 * n], o[2 * n + 1], o[2 * n + 2], o[2 * n + 3]);
      stsm2(ob + ((lane & 7) + ((lane >> 3) & 1) * 8) * 144 + 96, o[12], o[13]);
      __syncwarp();
#pragma unroll
      for (int u = 0; u < 4; u++) {
        const int idx = lane + 32 * u;
        if (idx < 112) {
          const int r = idx / 7, cc = idx - r * 7;
          const uint4 v = lds128(ob + r * 144 + cc * 16);
          *(uint4*)(p.out + (size_t)(ti * 128 + 16 * warp + r) * DM + 56 * tj + cc * 8) = v;
        }
      }
    }
    if (tid == 0) g_epoch[bid] = ep;
    TS(29 + wg);
  }
  asm volatile("barrier.cluster.arrive.aligned;" ::: "memory");
  asm volatile("barrier.cluster.wait.aligned;" ::: "memory");
}

typedef CUresult (*EncodeFn)(CUtensorMap*, CUtensorMapDataType, cuuint32_t, void*, const cuuint64_t*, const cuuint64_t*, const cuuint32_t*,
                             const cuuint32_t*, CUtensorMapInterleave, CUtensorMapSwizzle, CUtensorMapL2promotion, CUtensorMapFloatOOBfill);

}

extern "C" void kernel_launch(void* const* d_in, const int* in_sizes, int n_in, void* d_out, int out_size) {
  (void)in_sizes; (void)n_in; (void)out_size;
  static EncodeFn enc = nullptr;
  if (!enc) {
    void* fn = nullptr;
    cudaDriverEntryPointQueryResult qr;
    cudaGetDriverEntryPoint("cuTensorMapEncodeTiled", &fn, cudaEnableDefault, &qr);
    enc = (EncodeFn)fn;
    cudaFuncSetAttribute(fused_block_kernel, cudaFuncAttributeMaxDynamicSharedMemorySize, SMEM_BYTES);
  }
  Params p;
  p.x = (const __nv_bfloat16*)d_in[0];
  p.a_re = (const __nv_bfloat16*)d_in[1]; p.a_im = (const __nv_bfloat16*)d_in[2];
  p.b_re = (const __nv_bfloat16*)d_in[3]; p.b_im = (const __nv_bfloat16*)d_in[4];
  p.c_re = (const __nv_bfloat16*)d_in[5]; p.c_im = (const __nv_bfloat16*)d_in[6];
  p.log_dt = (const __nv_bfloat16*)d_in[7]; p.dskip = (const __nv_bfloat16*)d_in[8];
  p.w_in = (const __nv_bfloat16*)d_in[10]; p.w_sp = (const __nv_bfloat16*)d_in[11];
  p.b_sp = (const __nv_bfloat16*)d_in[12]; p.w_out = (const __nv_bfloat16*)d_in[13];
  p.cvec = (const __nv_bfloat16*)d_in[14]; p.w_mod = (const __nv_bfloat16*)d_in[15];
  p.out = (__nv_bfloat16*)d_out;
  CUtensorMap tm_wsp, tm_wout;
  {
    cuuint64_t gd[2] = {SEQ, SEQ}, gs[1] = {SEQ * 2};
    cuuint32_t box[2] = {64, 64}, es[2] = {1, 1};
    enc(&tm_wsp, CU_TENSOR_MAP_DATA_TYPE_BFLOAT16, 2, d_in[11], gd, gs, box, es, CU_TENSOR_MAP_INTERLEAVE_NONE, CU_TENSOR_MAP_SWIZZLE_128B,
        CU_TENSOR_MAP_L2_PROMOTION_L2_128B, CU_TENSOR_MAP_FLOAT_OOB_FILL_NONE);
  }
  {
    cuuint64_t gd[2] = {DM, FH}, gs[1] = {DM * 2};
    cuuint32_t box[2] = {64, 112}, es[2] = {1, 1};
    enc(&tm_wout, CU_TENSOR_MAP_DATA_TYPE_BFLOAT16, 2, d_in[13], gd, gs, box, es, CU_TENSOR_MAP_INTERLEAVE_NONE, CU_TENSOR_MAP_SWIZZLE_128B,
        CU_TENSOR_MAP_L2_PROMOTION_L2_128B, CU_TENSOR_MAP_FLOAT_OOB_FILL_NONE);
  }
  fused_block_kernel<<<NCTA, NTHREADS, SMEM_BYTES>>>(tm_wsp, tm_wout, p);
}
```

```cpp
#include <cuda_runtime.h>
#include <cuda.h>
#include <cuda_bf16.h>
#include <stdint.h>

namespace {

constexpr int SEQ = 2048, DM = 448, NMODE = 256, FF = 1792, FH = 896;
constexpr int NCTA = 128, NCONV = 112, NTHREADS = 384;
constexpr int NA = 7, NB = 5;
constexpr uint32_t A_SLOT = 16384, B_SLOT = 14336;
constexpr uint32_t OFF_A = 0;
constexpr uint32_t OFF_B = OFF_A + NA * A_SLOT;
constexpr uint32_t OFF_STG = OFF_B + NB * B_SLOT;
constexpr uint32_t OFF_MISC = OFF_STG + 28672;
constexpr uint32_t SMEM_BYTES = 232448;
constexpr uint32_t GEN_PITCH = 144, GEN_BYTES = 56 * GEN_PITCH;
constexpr uint32_t OFF_GEN01 = 0;
constexpr uint32_t OFF_GEN2 = OFF_B;
constexpr uint32_t OFF_RED = 49152;
constexpr uint32_t KTAB_CH = 2080 * 4, KTAB_ODD = 1040 * 4;
constexpr uint32_t OFF_KTAB = OFF_B - 4 * KTAB_CH;
constexpr uint32_t H_HI = 2240, H_CH = 4480;
constexpr uint32_t OFF_H = OFF_STG;
constexpr uint32_t OFF_X = OFF_MISC + 1024;
constexpr uint32_t OFF_BAR = OFF_MISC;
constexpr uint32_t OFF_T0 = OFF_MISC + 1024;
constexpr uint32_t OFF_CSB = OFF_T0;
constexpr uint32_t OFF_ST2 = OFF_T0 + 2048;
constexpr uint32_t OFF_GB = OFF_T0 + 6144;
constexpr uint32_t OFF_WIN = 0;
constexpr uint32_t OFF_AUXR = 100352;
constexpr uint32_t OFF_AUXS = OFF_STG;

constexpr unsigned SPIN_LIMIT = 1u << 22;

__device__ uint32_t g_epoch[NCTA];
__device__ uint2 g_st1[SEQ];
__device__ uint2 g_modw[6 * DM];
__device__ uint4 g_wp[16 * 7 * 896];
__device__ float2 g_csb[FF];
__device__ uint4 g_x1[16 * 7 * 1024];
__device__ uint4 g_st3[16 * 8 * 128];
__device__ uint4 g_z2[8 * 32 * 896];
__device__ uint4 g_gt[16 * 8 * 1792];
__device__ uint32_t g_cnt_x1[7 * 32];
__device__ uint32_t g_flag_wp[16 * 8];
__device__ uint32_t g_flag_z2[8 * 32 * 8];
__device__ uint32_t g_flag_gt[16 * 8 * 2 * 8];
#define TS(n) do {} while (0)

struct Params {
  const __nv_bfloat16 *x, *a_re, *a_im, *b_re, *b_im, *c_re, *c_im, *log_dt, *dskip, *w_in, *w_sp, *b_sp, *w_out, *cvec, *w_mod;
  __nv_bfloat16* out;
};

__device__ __forceinline__ uint32_t s2u(const void* p) { return (uint32_t)__cvta_generic_to_shared(p); }
__device__ __forceinline__ void mbar_init(uint32_t b, uint32_t c) { asm volatile("mbarrier.init.shared::cta.b64 [%0], %1;" ::"r"(b), "r"(c)); }
__device__ __forceinline__ void mbar_expect(uint32_t b, uint32_t n) { asm volatile("mbarrier.arrive.expect_tx.shared::cta.b64 _, [%0], %1;" ::"r"(b), "r"(n) : "memory"); }
__device__ __forceinline__ void mbar_wait(uint32_t b, uint32_t ph) {
  asm volatile(
      "{.reg .pred p; .reg .u32 c; mov.u32 c, 0;\n"
      "LW: mbarrier.try_wait.parity.shared::cta.b64 p, [%0], %1; @p bra LD;\n"
      "add.u32 c, c, 1; setp.lt.u32 p, c, 4194304; @p bra LW;\n"
      "LD: }" ::"r"(b), "r"(ph) : "memory");
}
__device__ __forceinline__ void mbar_arrive(uint32_t b) { asm volatile("mbarrier.arrive.shared::cta.b64 _, [%0];" ::"r"(b) : "memory"); }
__device__ __forceinline__ void mbar_arrive_cluster(uint32_t b, uint32_t cta) {
  asm volatile("{.reg .b32 r; mapa.shared::cluster.u32 r, %0, %1; mbarrier.arrive.shared::cluster.b64 _, [r];}" ::"r"(b), "r"(cta) : "memory");
}
__device__ __forceinline__ bool elect() { uint32_t e; asm volatile("{.reg .pred p; elect.sync _|p, 0xffffffff; selp.u32 %0,1,0,p;}" : "=r"(e)); return e != 0; }
__device__ __forceinline__ void bar_sync(int id, int n) { asm volatile("bar.sync %0, %1;" ::"r"(id), "r"(n) : "memory"); }
__device__ __forceinline__ void bar_arrive(int id, int n) { asm volatile("bar.arrive %0, %1;" ::"r"(id), "r"(n) : "memory"); }
__device__ __forceinline__ void fence_async_smem() { asm volatile("fence.proxy.async.shared::cta;" ::: "memory"); }
__device__ __forceinline__ void fence_async_all() { asm volatile("fence.proxy.async;" ::: "memory"); }
__device__ __forceinline__ void fence_gpu() { asm volatile("fence.acq_rel.gpu;" ::: "memory"); }
__device__ __forceinline__ void wg_fence() { asm volatile("wgmma.fence.sync.aligned;" ::: "memory"); }
__device__ __forceinline__ void wg_commit() { asm volatile("wgmma.commit_group.sync.aligned;" ::: "memory"); }
template <int N> __device__ __forceinline__ void wg_wait() { asm volatile("wgmma.wait_group.sync.aligned %0;" ::"n"(N) : "memory"); }

__device__ __forceinline__ uint32_t ld_acq(const uint32_t* p) { uint32_t v; asm volatile("ld.acquire.gpu.global.u32 %0, [%1];" : "=r"(v) : "l"(p) : "memory"); return v; }
__device__ __forceinline__ void st_rel(uint32_t* p, uint32_t v) { asm volatile("st.release.gpu.global.u32 [%0], %1;" ::"l"(p), "r"(v) : "memory"); }
__device__ __forceinline__ void red_rel(uint32_t* p, uint32_t v) { asm volatile("red.release.gpu.global.add.u32 [%0], %1;" ::"l"(p), "r"(v) : "memory"); }
__device__ __forceinline__ uint2 ld_rlx2(const uint2* p) { uint2 v; asm volatile("ld.relaxed.gpu.global.v2.u32 {%0,%1}, [%2];" : "=r"(v.x), "=r"(v.y) : "l"(p) : "memory"); return v; }
__device__ __forceinline__ uint4 ld_rlx4(const void* p) { uint4 v; asm volatile("ld.relaxed.gpu.global.v4.u32 {%0,%1,%2,%3}, [%4];" : "=r"(v.x), "=r"(v.y), "=r"(v.z), "=r"(v.w) : "l"(p) : "memory"); return v; }
__device__ __forceinline__ void st_rlx2(uint2* p, uint32_t a, uint32_t b) { asm volatile("st.relaxed.gpu.global.v2.u32 [%0], {%1,%2};" ::"l"(p), "r"(a), "r"(b) : "memory"); }
__device__ __forceinline__ void st_rlx4(uint4* p, uint32_t a, uint32_t b, uint32_t c, uint32_t d) { asm volatile("st.relaxed.gpu.global.v4.u32 [%0], {%1,%2,%3,%4};" ::"l"(p), "r"(a), "r"(b), "r"(c), "r"(d) : "memory"); }
__device__ __forceinline__ void wait_flag(const uint32_t* p, uint32_t target) {
  unsigned it = 0;
  while ((int)(ld_acq(p) - target) < 0 && ++it < SPIN_LIMIT) {}
}
__device__ __forceinline__ float wait_modw(const uint2* p, uint32_t ep) {
  unsigned it = 0;
  uint2 v = ld_rlx2(p);
  while (v.y != ep && ++it < SPIN_LIMIT) v = ld_rlx2(p);
  return __uint_as_float(v.x);
}

__device__ __forceinline__ void bulk_g2s(uint32_t dst, const void* src, uint32_t bytes, uint32_t bar) {
  asm volatile("cp.async.bulk.shared::cluster.global.mbarrier::complete_tx::bytes [%0], [%1], %2, [%3];" ::"r"(dst), "l"(src), "r"(bytes), "r"(bar) : "memory");
}
__device__ __forceinline__ void bulk_g2s_mc(uint32_t dst, const void* src, uint32_t bytes, uint32_t bar) {
  asm volatile("cp.async.bulk.shared::cluster.global.mbarrier::complete_tx::bytes.multicast::cluster [%0], [%1], %2, [%3], %4;" ::"r"(dst), "l"(src), "r"(bytes), "r"(bar), "h"((uint16_t)3) : "memory");
}
__device__ __forceinline__ void tma2d(uint32_t dst, const CUtensorMap* tm, int c0, int c1, uint32_t bar) {
  asm volatile("cp.async.bulk.tensor.2d.shared::cluster.global.mbarrier::complete_tx::bytes [%0], [%1, {%3, %4}], [%2];" ::"r"(dst), "l"(tm), "r"(bar), "r"(c0), "r"(c1) : "memory");
}
__device__ __forceinline__ void tma2d_mc(uint32_t dst, const CUtensorMap* tm, int c0, int c1, uint32_t bar) {
  asm volatile("cp.async.bulk.tensor.2d.shared::cluster.global.mbarrier::complete_tx::bytes.multicast::cluster [%0], [%1, {%3, %4}], [%2], %5;" ::"r"(dst), "l"(tm), "r"(bar), "r"(c0), "r"(c1), "h"((uint16_t)3) : "memory");
}
__device__ __forceinline__ void bulk_s2g(void* dst, uint32_t src, uint32_t bytes) {
  asm volatile("cp.async.bulk.global.shared::cta.bulk_group [%0], [%1], %2;" ::"l"(dst), "r"(src), "r"(bytes) : "memory");
  asm volatile("cp.async.bulk.commit_group;" ::: "memory");
  asm volatile("cp.async.bulk.wait_group 0;" ::: "memory");
}
__device__ __forceinline__ void prefetch_l2(const void* p, uint32_t bytes) { asm volatile("cp.async.bulk.prefetch.L2.global [%0], %1;" ::"l"(p), "r"(bytes) : "memory"); }

__device__ __forceinline__ uint32_t lds32(uint32_t a) { uint32_t v; asm volatile("ld.shared.u32 %0, [%1];" : "=r"(v) : "r"(a)); return v; }
__device__ __forceinline__ uint32_t lds16(uint32_t a) { uint16_t v; asm volatile("ld.shared.u16 %0, [%1];" : "=h"(v) : "r"(a)); return v; }
__device__ __forceinline__ float ldsf(uint32_t a) { float v; asm volatile("ld.shared.f32 %0, [%1];" : "=f"(v) : "r"(a)); return v; }
__device__ __forceinline__ float2 lds2f(uint32_t a) { float2 v; asm volatile("ld.shared.v2.f32 {%0,%1}, [%2];" : "=f"(v.x), "=f"(v.y) : "r"(a)); return v; }
__device__ __forceinline__ float4 lds4f(uint32_t a) { float4 v; asm volatile("ld.shared.v4.f32 {%0,%1,%2,%3}, [%4];" : "=f"(v.x), "=f"(v.y), "=f"(v.z), "=f"(v.w) : "r"(a)); return v; }
__device__ __forceinline__ uint4 lds128(uint32_t a) { uint4 v; asm volatile("ld.shared.v4.u32 {%0,%1,%2,%3}, [%4];" : "=r"(v.x), "=r"(v.y), "=r"(v.z), "=r"(v.w) : "r"(a)); return v; }
__device__ __forceinline__ void sts32(uint32_t a, uint32_t v) { asm volatile("st.shared.u32 [%0], %1;" ::"r"(a), "r"(v) : "memory"); }
__device__ __forceinline__ void stsf(uint32_t a, float v) { asm volatile("st.shared.f32 [%0], %1;" ::"r"(a), "f"(v) : "memory"); }
__device__ __forceinline__ void sts2f(uint32_t a, float x, float y) { asm volatile("st.shared.v2.f32 [%0], {%1,%2};" ::"r"(a), "f"(x), "f"(y) : "memory"); }
__device__ __forceinline__ void sts4f(uint32_t a, float x, float y, float z, float w) { asm volatile("st.shared.v4.f32 [%0], {%1,%2,%3,%4};" ::"r"(a), "f"(x), "f"(y), "f"(z), "f"(w) : "memory"); }
__device__ __forceinline__ void sts128(uint32_t a, uint32_t x, uint32_t y, uint32_t z, uint32_t w) { asm volatile("st.shared.v4.u32 [%0], {%1,%2,%3,%4};" ::"r"(a), "r"(x), "r"(y), "r"(z), "r"(w) : "memory"); }
__device__ __forceinline__ void ldsm4(uint32_t a, uint32_t& r0, uint32_t& r1, uint32_t& r2, uint32_t& r3) { asm volatile("ldmatrix.sync.aligned.m8n8.x4.shared.b16 {%0,%1,%2,%3}, [%4];" : "=r"(r0), "=r"(r1), "=r"(r2), "=r"(r3) : "r"(a) : "memory"); }
__device__ __forceinline__ void ldsm2(uint32_t a, uint32_t& r0, uint32_t& r1) { asm volatile("ldmatrix.sync.aligned.m8n8.x2.shared.b16 {%0,%1}, [%2];" : "=r"(r0), "=r"(r1) : "r"(a) : "memory"); }
__device__ __forceinline__ void ldsm4t(uint32_t a, uint32_t& r0, uint32_t& r1, uint32_t& r2, uint32_t& r3) { asm volatile("ldmatrix.sync.aligned.m8n8.x4.trans.shared.b16 {%0,%1,%2,%3}, [%4];" : "=r"(r0), "=r"(r1), "=r"(r2), "=r"(r3) : "r"(a) : "memory"); }
__device__ __forceinline__ void stsm4(uint32_t a, uint32_t r0, uint32_t r1, uint32_t r2, uint32_t r3) { asm volatile("stmatrix.sync.aligned.m8n8.x4.shared.b16 [%0], {%1,%2,%3,%4};" ::"r"(a), "r"(r0), "r"(r1), "r"(r2), "r"(r3) : "memory"); }
__device__ __forceinline__ void stsm2(uint32_t a, uint32_t r0, uint32_t r1) { asm volatile("stmatrix.sync.aligned.m8n8.x2.shared.b16 [%0], {%1,%2};" ::"r"(a), "r"(r0), "r"(r1) : "memory"); }
__device__ __forceinline__ void stsm4t(uint32_t a, uint32_t r0, uint32_t r1, uint32_t r2, uint32_t r3) { asm volatile("stmatrix.sync.aligned.m8n8.x4.trans.shared.b16 [%0], {%1,%2,%3,%4};" ::"r"(a), "r"(r0), "r"(r1), "r"(r2), "r"(r3) : "memory"); }
__device__ __forceinline__ void mma16816(float* d, uint32_t a0, uint32_t a1, uint32_t a2, uint32_t a3, uint32_t b0, uint32_t b1) {
  asm volatile("mma.sync.aligned.m16n8k16.row.col.f32.bf16.bf16.f32 {%0,%1,%2,%3}, {%4,%5,%6,%7}, {%8,%9}, {%0,%1,%2,%3};"
               : "+f"(d[0]), "+f"(d[1]), "+f"(d[2]), "+f"(d[3]) : "r"(a0), "r"(a1), "r"(a2), "r"(a3), "r"(b0), "r"(b1));
}

__device__ __forceinline__ uint32_t pack_bf16(float lo, float hi) { uint32_t r; asm("cvt.rn.bf16x2.f32 %0, %1, %2;" : "=r"(r) : "f"(hi), "f"(lo)); return r; }
__device__ __forceinline__ float bf_lo(uint32_t v) { return __uint_as_float(v << 16); }
__device__ __forceinline__ float bf_hi(uint32_t v) { return __uint_as_float(v & 0xffff0000u); }
__device__ __forceinline__ float round_bf16(float x) { return bf_lo(pack_bf16(x, 0.f)); }
__device__ __forceinline__ uint32_t bf2_mul(uint32_t a, uint32_t b) { uint32_t r; asm("mul.rn.bf16x2 %0, %1, %2;" : "=r"(r) : "r"(a), "r"(b)); return r; }
__device__ __forceinline__ uint32_t bf2_add(uint32_t a, uint32_t b) { uint32_t r; asm("add.rn.bf16x2 %0, %1, %2;" : "=r"(r) : "r"(a), "r"(b)); return r; }
__device__ __forceinline__ uint32_t bf2_sub(uint32_t a, uint32_t b) { uint32_t r; asm("sub.rn.bf16x2 %0, %1, %2;" : "=r"(r) : "r"(a), "r"(b)); return r; }
__device__ __forceinline__ uint32_t dup_bf16(float v) { return pack_bf16(v, v); }
__device__ __forceinline__ float ldg_bf16(const __nv_bfloat16* p) { return __uint_as_float((uint32_t)__ldg(reinterpret_cast<const unsigned short*>(p)) << 16); }
__device__ __forceinline__ float gelu_tanh(float x) {
  float u = x * fmaf(0.0356774081f, x * x, 0.7978845608f);
  float t; asm("tanh.approx.f32 %0, %1;" : "=f"(t) : "f"(u));
  float hx = 0.5f * x;
  return fmaf(hx, t, hx);
}

__device__ __forceinline__ uint64_t desc_sw128(uint32_t addr) { return (uint64_t)((addr & 0x3FFFF) >> 4) | ((uint64_t)1 << 16) | ((uint64_t)64 << 32) | ((uint64_t)1 << 62); }
__device__ __forceinline__ uint64_t desc_nosw(uint32_t addr, uint32_t lbo, uint32_t sbo) { return (uint64_t)((addr & 0x3FFFF) >> 4) | ((uint64_t)(lbo >> 4) << 16) | ((uint64_t)(sbo >> 4) << 32); }

__device__ __forceinline__ void wgmma_n112_tA(float* d, uint64_t da, uint64_t db, int sd) {
  asm volatile("{.reg .pred p; setp.ne.b32 p, %58, 0;\n"
    "wgmma.mma_async.sync.aligned.m64n112k16.f32.bf16.bf16 {%0,%1,%2,%3,%4,%5,%6,%7,%8,%9,%10,%11,%12,%13,%14,%15,%16,%17,%18,%19,%20,%21,%22,%23,%24,%25,%26,%27,%28,%29,%30,%31,%32,%33,%34,%35,%36,%37,%38,%39,%40,%41,%42,%43,%44,%45,%46,%47,%48,%49,%50,%51,%52,%53,%54,%55}, %56, %57, p, 1, 1, 1, 0;}"
    : "+f"(d[0]),"+f"(d[1]),"+f"(d[2]),"+f"(d[3]),"+f"(d[4]),"+f"(d[5]),"+f"(d[6]),"+f"(d[7]),"+f"(d[8]),"+f"(d[9]),"+f"(d[10]),"+f"(d[11]),"+f"(d[12]),"+f"(d[13]),"+f"(d[14]),"+f"(d[15]),"+f"(d[16]),"+f"(d[17]),"+f"(d[18]),"+f"(d[19]),"+f"(d[20]),"+f"(d[21]),"+f"(d[22]),"+f"(d[23]),"+f"(d[24]),"+f"(d[25]),"+f"(d[26]),"+f"(d[27]),"+f"(d[28]),"+f"(d[29]),"+f"(d[30]),"+f"(d[31]),"+f"(d[32]),"+f"(d[33]),"+f"(d[34]),"+f"(d[35]),"+f"(d[36]),"+f"(d[37]),"+f"(d[38]),"+f"(d[39]),"+f"(d[40]),"+f"(d[41]),"+f"(d[42]),"+f"(d[43]),"+f"(d[44]),"+f"(d[45]),"+f"(d[46]),"+f"(d[47]),"+f"(d[48]),"+f"(d[49]),"+f"(d[50]),"+f"(d[51]),"+f"(d[52]),"+f"(d[53]),"+f"(d[54]),"+f"(d[55])
    : "l"(da), "l"(db), "r"(sd));
}
__device__ __forceinline__ void wgmma_n112(float* d, uint64_t da, uint64_t db, int sd) {
  asm volatile("{.reg .pred p; setp.ne.b32 p, %58, 0;\n"
    "wgmma.mma_async.sync.aligned.m64n112k16.f32.bf16.bf16 {%0,%1,%2,%3,%4,%5,%6,%7,%8,%9,%10,%11,%12,%13,%14,%15,%16,%17,%18,%19,%20,%21,%22,%23,%24,%25,%26,%27,%28,%29,%30,%31,%32,%33,%34,%35,%36,%37,%38,%39,%40,%41,%42,%43,%44,%45,%46,%47,%48,%49,%50,%51,%52,%53,%54,%55}, %56, %57, p, 1, 1, 0, 0;}"
    : "+f"(d[0]),"+f"(d[1]),"+f"(d[2]),"+f"(d[3]),"+f"(d[4]),"+f"(d[5]),"+f"(d[6]),"+f"(d[7]),"+f"(d[8]),"+f"(d[9]),"+f"(d[10]),"+f"(d[11]),"+f"(d[12]),"+f"(d[13]),"+f"(d[14]),"+f"(d[15]),"+f"(d[16]),"+f"(d[17]),"+f"(d[18]),"+f"(d[19]),"+f"(d[20]),"+f"(d[21]),"+f"(d[22]),"+f"(d[23]),"+f"(d[24]),"+f"(d[25]),"+f"(d[26]),"+f"(d[27]),"+f"(d[28]),"+f"(d[29]),"+f"(d[30]),"+f"(d[31]),"+f"(d[32]),"+f"(d[33]),"+f"(d[34]),"+f"(d[35]),"+f"(d[36]),"+f"(d[37]),"+f"(d[38]),"+f"(d[39]),"+f"(d[40]),"+f"(d[41]),"+f"(d[42]),"+f"(d[43]),"+f"(d[44]),"+f"(d[45]),"+f"(d[46]),"+f"(d[47]),"+f"(d[48]),"+f"(d[49]),"+f"(d[50]),"+f"(d[51]),"+f"(d[52]),"+f"(d[53]),"+f"(d[54]),"+f"(d[55])
    : "l"(da), "l"(db), "r"(sd));
}
__device__ __forceinline__ void wgmma_n56_tB(float* d, uint64_t da, uint64_t db, int sd) {
  asm volatile("{.reg .pred p; setp.ne.b32 p, %30, 0;\n"
    "wgmma.mma_async.sync.aligned.m64n56k16.f32.bf16.bf16 {%0,%1,%2,%3,%4,%5,%6,%7,%8,%9,%10,%11,%12,%13,%14,%15,%16,%17,%18,%19,%20,%21,%22,%23,%24,%25,%26,%27}, %28, %29, p, 1, 1, 0, 1;}"
    : "+f"(d[0]),"+f"(d[1]),"+f"(d[2]),"+f"(d[3]),"+f"(d[4]),"+f"(d[5]),"+f"(d[6]),"+f"(d[7]),"+f"(d[8]),"+f"(d[9]),"+f"(d[10]),"+f"(d[11]),"+f"(d[12]),"+f"(d[13]),"+f"(d[14]),"+f"(d[15]),"+f"(d[16]),"+f"(d[17]),"+f"(d[18]),"+f"(d[19]),"+f"(d[20]),"+f"(d[21]),"+f"(d[22]),"+f"(d[23]),"+f"(d[24]),"+f"(d[25]),"+f"(d[26]),"+f"(d[27])
    : "l"(da), "l"(db), "r"(sd));
}
__device__ __forceinline__ void wgmma_rs32(float* d, uint32_t a0, uint32_t a1, uint32_t a2, uint32_t a3, uint64_t db, int sd) {
  asm volatile("{.reg .pred p; setp.ne.b32 p, %21, 0;\n"
    "wgmma.mma_async.sync.aligned.m64n32k16.f32.bf16.bf16 {%0,%1,%2,%3,%4,%5,%6,%7,%8,%9,%10,%11,%12,%13,%14,%15}, {%16,%17,%18,%19}, %20, p, 1, 1, 0;}"
    : "+f"(d[0]),"+f"(d[1]),"+f"(d[2]),"+f"(d[3]),"+f"(d[4]),"+f"(d[5]),"+f"(d[6]),"+f"(d[7]),"+f"(d[8]),"+f"(d[9]),"+f"(d[10]),"+f"(d[11]),"+f"(d[12]),"+f"(d[13]),"+f"(d[14]),"+f"(d[15])
    : "r"(a0), "r"(a1), "r"(a2), "r"(a3), "l"(db), "r"(sd));
}

enum { BAR_WG0 = 1, BAR_WG1 = 2, BAR_WG2 = 3, BAR_CONS = 4, BAR_K2 = 5, BAR_K3 = 6, BAR_RED0 = 7, BAR_RED1 = 8, BAR_AUX = 9 };

struct Cplx { float r, i; };
__device__ __forceinline__ Cplx cmul(Cplx a, Cplx b) { Cplx o; o.r = fmaf(a.r, b.r, -a.i * b.i); o.i = fmaf(a.r, b.i, a.i * b.r); return o; }
__device__ __forceinline__ Cplx cexp_scaled(float ar2, float air, float s) {
  float m; asm("ex2.approx.ftz.f32 %0, %1;" : "=f"(m) : "f"(ar2 * s));
  float rev = air * s; rev -= rintf(rev);
  float ang = rev * 6.283185307179586f;
  Cplx o; o.r = m * __cosf(ang); o.i = m * __sinf(ang); return o;
}

struct GenParams { uint32_t are, aim, bre, bim, cre, cim; float dt; };
__device__ __forceinline__ GenParams load_gen_params(const Params& p, int d, int tw) {
  GenParams g; size_t o = (size_t)d * NMODE + 2 * tw;
  g.are = __ldg((const uint32_t*)(p.a_re + o)); g.aim = __ldg((const uint32_t*)(p.a_im + o));
  g.bre = __ldg((const uint32_t*)(p.b_re + o)); g.bim = __ldg((const uint32_t*)(p.b_im + o));
  g.cre = __ldg((const uint32_t*)(p.c_re + o)); g.cim = __ldg((const uint32_t*)(p.c_im + o));
  g.dt = ldg_bf16(p.log_dt + d);
  return g;
}

__device__ __forceinline__ void gen_kernel(const GenParams& gp, uint32_t wgbuf, uint32_t ktab, int tw, int barid) {
  const int lane = tw & 31, wp = tw >> 5, g = lane >> 2, c = lane & 3;
  const uint32_t buf = wgbuf + wp * GEN_BYTES;
  const float dt = round_bf16(__expf(gp.dt));
  float acc[2][3][4];
#pragma unroll
  for (int a = 0; a < 2; a++)
#pragma unroll
    for (int b = 0; b < 3; b++)
#pragma unroll
      for (int e = 0; e < 4; e++) acc[a][b][e] = 0.f;
#pragma unroll 1
  for (int rnd = 0; rnd < 2; rnd++) {
    const float are = rnd ? bf_hi(gp.are) : bf_lo(gp.are), aim = rnd ? bf_hi(gp.aim) : bf_lo(gp.aim);
    const float bre = dt * (rnd ? bf_hi(gp.bre) : bf_lo(gp.bre)), bim = dt * (rnd ? bf_hi(gp.bim) : bf_lo(gp.bim));
    const float cre = rnd ? bf_hi(gp.cre) : bf_lo(gp.cre), cim = rnd ? bf_hi(gp.cim) : bf_lo(gp.cim);
    const float ar2 = (dt * are) * 1.4426950408889634f, air = (dt * aim) * 0.15915494309189535f;
    Cplx cf; cf.r = cre * bre - cim * bim; cf.i = cre * bim + cim * bre;
    const Cplx z1 = cexp_scaled(ar2, air, 1.f), z256 = cexp_scaled(ar2, air, 256.f);
    Cplx w = cexp_scaled(ar2, air, 8.f); w.i = -w.i;
    const uint32_t col = buf + lane * 4;
    Cplx w2 = cmul(w, w), e0, e1 = w; e0.r = 1.f; e0.i = 0.f;
#pragma unroll
    for (int j = 0; j < 32; j += 2) {
      sts32(col + j * GEN_PITCH, pack_bf16(e0.r, e0.i));
      sts32(col + (j + 1) * GEN_PITCH, pack_bf16(e1.r, e1.i));
      if (j < 30) { e0 = (j == 0) ? w2 : cmul(e0, w2); e1 = cmul(e1, w2); }
    }
    Cplx xv[8]; xv[0] = cf;
#pragma unroll
    for (int i = 1; i < 8; i++) xv[i] = cmul(xv[i - 1], z1);
#pragma unroll
    for (int i = 0; i < 8; i++) sts32(col + (32 + i) * GEN_PITCH, pack_bf16(xv[i].r, xv[i].i));
    Cplx y0 = cmul(xv[0], z256), y2 = cmul(xv[2], z256), y4 = cmul(xv[4], z256), y6 = cmul(xv[6], z256);
    sts32(col + 40 * GEN_PITCH, pack_bf16(y0.r, y0.i)); sts32(col + 41 * GEN_PITCH, pack_bf16(y2.r, y2.i));
    sts32(col + 42 * GEN_PITCH, pack_bf16(y4.r, y4.i)); sts32(col + 43 * GEN_PITCH, pack_bf16(y6.r, y6.i));
    y0 = cmul(y0, z256); y4 = cmul(y4, z256);
    sts32(col + 44 * GEN_PITCH, pack_bf16(y0.r, y0.i)); sts32(col + 45 * GEN_PITCH, pack_bf16(y4.r, y4.i));
    y0 = cmul(y0, z256); y4 = cmul(y4, z256);
    sts32(col + 46 * GEN_PITCH, pack_bf16(y0.r, y0.i)); sts32(col + 47 * GEN_PITCH, pack_bf16(y4.r, y4.i));
#pragma unroll
    for (int i = 0; i < 5; i++) { y0 = cmul(y0, z256); sts32(col + (48 + i) * GEN_PITCH, pack_bf16(y0.r, y0.i)); }
    __syncwarp();
    const uint32_t aaddr = buf + ((lane & 7) + ((lane >> 3) & 1) * 8) * GEN_PITCH + (lane >> 4) * 16;
    const uint32_t baddr = buf + (32 + (lane & 7) + (lane >> 4) * 8) * GEN_PITCH + ((lane >> 3) & 1) * 16;
    const uint32_t baddr2 = buf + (48 + (lane & 7)) * GEN_PITCH + ((lane >> 3) & 1) * 16;
#pragma unroll
    for (int ks = 0; ks < 4; ks++) {
      uint32_t a0[4], a1[4], b[6];
      ldsm4(aaddr + ks * 32, a0[0], a0[1], a0[2], a0[3]);
      ldsm4(aaddr + 16 * GEN_PITCH + ks * 32, a1[0], a1[1], a1[2], a1[3]);
      ldsm4(baddr + ks * 32, b[0], b[1], b[2], b[3]);
      ldsm2(baddr2 + ks * 32, b[4], b[5]);
#pragma unroll
      for (int nt = 0; nt < 3; nt++) {
        mma16816(acc[0][nt], a0[0], a0[1], a0[2], a0[3], b[2 * nt], b[2 * nt + 1]);
        mma16816(acc[1][nt], a1[0], a1[1], a1[2], a1[3], b[2 * nt], b[2 * nt + 1]);
      }
    }
    __syncwarp();
  }
#pragma unroll
  for (int u = 0; u < 6; u++)
#pragma unroll
    for (int e = 0; e < 4; e++) stsf(buf + ((u * 4 + e) * 32 + lane) * 4, acc[u / 3][u % 3][e]);
  bar_sync(barid, 128);
  const uint32_t kd = wgbuf + 4096;
#pragma unroll
  for (int u = 0; u < 6; u++) {
    const uint32_t o = wgbuf + ((u * 4 + wp) * 32 + lane) * 4;
    const float s = (ldsf(o) + ldsf(o + GEN_BYTES)) + (ldsf(o + 2 * GEN_BYTES) + ldsf(o + 3 * GEN_BYTES));
    const int j = 16 * (u / 3) + g + 8 * (wp >> 1), i = 8 * (u % 3) + 2 * c + (wp & 1);
    int hi;
    if (u % 3 == 0) hi = i;
    else if (u % 3 == 1) hi = (i < 12) ? 256 + 2 * (i - 8) : 512 + 256 * ((i - 12) >> 1) + 4 * ((i - 12) & 1);
    else hi = 1024 + 256 * (i - 16);
    const int v = hi + 8 * j;
    const int idx = v < 128 ? v : (int)(__float_as_uint((float)v) >> 16) - 0x4300 + 128;
    if (v <= 2048) stsf(kd + idx * 4, s);
  }
  bar_sync(barid, 128);
  {
    float kv[17];
#pragma unroll
    for (int e = 0; e < 17; e++) {
      const int l = 16 * tw - 1 + e;
      const int idx = l < 128 ? l : (int)(pack_bf16((float)l, 0.f) & 0xffffu) - 0x4300 + 128;
      kv[e] = (l >= 0) ? ldsf(kd + max(idx, 0) * 4) : 0.f;
    }
    uint32_t pe[8], po[8];
#pragma unroll
    for (int u = 0; u < 8; u++) { pe[u] = pack_bf16(kv[2 * u + 1], kv[2 * u]); po[u] = pack_bf16(kv[2 * u + 2], kv[2 * u + 1]); }
    const uint32_t o = ktab + (8 + 8 * tw) * 4;
    sts128(o, pe[0], pe[1], pe[2], pe[3]); sts128(o + 16, pe[4], pe[5], pe[6], pe[7]);
    sts128(o + KTAB_ODD, po[0], po[1], po[2], po[3]); sts128(o + KTAB_ODD + 16, po[4], po[5], po[6], po[7]);
    if (tw < 4) sts128(ktab + (tw & 1) * 16 + (tw >> 1) * KTAB_ODD, 0, 0, 0, 0);
  }
}

__device__ __forceinline__ void ln1_stats(const uint32_t (&v)[2][7], int row0, int lane, uint32_t ep) {
#pragma unroll
  for (int r = 0; r < 2; r++) {
    float s = 0.f;
#pragma unroll
    for (int k = 0; k < 7; k++) s += bf_lo(v[r][k]) + bf_hi(v[r][k]);
#pragma unroll
    for (int o = 16; o; o >>= 1) s += __shfl_xor_sync(0xffffffffu, s, o);
    const float mean = s * (1.f / DM);
    float q = 0.f;
#pragma unroll
    for (int k = 0; k < 7; k++) { float a = bf_lo(v[r][k]) - mean, b = bf_hi(v[r][k]) - mean; q = fmaf(a, a, fmaf(b, b, q)); }
#pragma unroll
    for (int o = 16; o; o >>= 1) q += __shfl_xor_sync(0xffffffffu, q, o);
    const float sd = sqrtf(round_bf16(round_bf16(q * (1.f / DM)) + 1e-5f));
    if (lane == 0) st_rlx2(&g_st1[row0 + r], pack_bf16(mean, sd), ep);
  }
}

__device__ __forceinline__ void conv_channel(uint32_t sb, int q, int cidx, int tw, int wg, int round, uint32_t dsk2, uint32_t ga2) {
  const int lane = tw & 31, h = tw >> 5, g = lane >> 2, c = lane & 3;
  const uint32_t kt = sb + OFF_KTAB + q * KTAB_CH + (g & 1) * KTAB_ODD + (8 + 64 * h + (g >> 1) - c - 4) * 4;
  const uint32_t hb = sb + OFF_H + q * H_CH;
  const uint64_t db = desc_nosw(hb + 8 * 16, H_HI, 128);
  float acc[64];
  uint32_t wa[17], wb[17];
#define CONV_PASS(W, K)                                                                                                  \
  _Pragma("unroll") for (int e = 0; e < 17; e++) W[e] = lds32(kt + (K) * 1024 + e * 16);                                  \
  wg_fence();                                                                                                            \
  _Pragma("unroll") for (int s = 0; s < 8; s++)                                                                           \
    _Pragma("unroll") for (int G = 3; G >= (K); G--)                                                                      \
      wgmma_rs32(acc + 16 * G, W[2 * s + 1], W[2 * s + 2], W[2 * s], W[2 * s + 1], db + 32 * (G - (K)) - s, (K) + s != 0); \
  wg_commit();
  CONV_PASS(wa, 0)
  CONV_PASS(wb, 1)
  wg_wait<1>();
  CONV_PASS(wa, 2)
  wg_wait<1>();
  CONV_PASS(wb, 3)
  wg_wait<0>();
#undef CONV_PASS
  if (wg == 1) bar_sync(BAR_RED1, 256);
  else if (round == 1) bar_sync(BAR_RED0, 256);
  const uint32_t red = sb + OFF_RED + lane * 16;
  const int toff = (h * (33 - h)) >> 1;
#pragma unroll
  for (int nu = 0; nu < 16; nu++)
    if (nu + h <= 15) sts4f(red + (toff + nu) * 512, acc[4 * nu], acc[4 * nu + 1], acc[4 * nu + 2], acc[4 * nu + 3]);
  bar_sync(BAR_WG0 + wg, 128);
  float y[4][4];
#pragma unroll
  for (int ii = 0; ii < 4; ii++) {
    const int I = 4 * h + ii;
    float4 s = lds4f(red + I * 512);
#pragma unroll
    for (int hh = 1; hh < 4; hh++) {
      if (I - hh >= 0) {
        const float4 t = lds4f(red + (((hh * (33 - hh)) >> 1) + I - hh) * 512);
        s.x += t.x; s.y += t.y; s.z += t.z; s.w += t.w;
      }
    }
    y[ii][0] = s.x; y[ii][1] = s.y; y[ii][2] = s.z; y[ii][3] = s.w;
  }
  if (wg == 0) bar_arrive(BAR_RED1, 256);
  else if (round == 0) bar_arrive(BAR_RED0, 256);
  const uint32_t xb = sb + OFF_X + q * 4096;
  const int mrow = (lane & 7) + (lane >> 4) * 8, mhalf = (lane >> 3) & 1;
#pragma unroll
  for (int pp = 0; pp < 2; pp++) {
    const int blk = 32 * h + 16 * pp + mrow;
    uint32_t hv[4], xv[4], o[4];
    ldsm4t(hb + mhalf * H_HI + (8 + blk) * 16, hv[0], hv[1], hv[2], hv[3]);
    const uint32_t xa = xb + mhalf * 2048 + blk * 16;
    ldsm4t(xa, xv[0], xv[1], xv[2], xv[3]);
#pragma unroll
    for (int m = 0; m < 4; m++) {
      const float* yy = &y[2 * pp + (m >> 1)][2 * (m & 1)];
      const uint32_t ya = bf2_add(pack_bf16(yy[0], yy[1]), bf2_mul(hv[m], dsk2));
      o[m] = bf2_add(xv[m], bf2_mul(ga2, ya));
    }
    stsm4t(xa, o[0], o[1], o[2], o[3]);
  }
  __syncwarp();
  const int k = q * NCONV + cidx, kb = k >> 6, kr = k & 63;
#pragma unroll
  for (int u = 0; u < 2; u++) {
    const int ch = 64 * h + 32 * u + lane;
    const uint4 v = lds128(xb + (ch & 1) * 2048 + (ch >> 1) * 16);
    const int t64 = ch >> 3;
    g_x1[((t64 >> 1) * 7 + kb) * 1024 + (t64 & 1) * 512 + kr * 8 + ((ch & 7) ^ (kr & 7))] = v;
  }
  fence_async_all();
  bar_sync(BAR_WG0 + wg, 128);
  if (tw == 0) { fence_gpu(); red_rel(&g_cnt_x1[kb * 32], 1u); }
}

struct ModLoads { uint4 v[13]; };
__device__ __forceinline__ void mod_load(ModLoads& m, const Params& p, int col0, int tid) {
  const int ch = tid % 7, rg = tid / 7;
#pragma unroll
  for (int k = 0; k < 13; k++) {
    const int r = rg + 36 * k;
    m.v[k] = (tid < 252 && r < DM) ? __ldg((const uint4*)(p.w_mod + (size_t)r * (6 * DM) + col0 + ch * 8)) : make_uint4(0, 0, 0, 0);
  }
}
__device__ __forceinline__ void mod_finish(const ModLoads& m, uint32_t sb, int col0, int tid, uint32_t ep) {
  const int ch = tid % 7, rg = tid / 7;
  float a[8];
#pragma unroll
  for (int e = 0; e < 8; e++) a[e] = 0.f;
#pragma unroll
  for (int k = 0; k < 13; k++) {
    const int r = min(rg + 36 * k, DM - 1);
    const float s = ldsf(sb + OFF_AUXS + r * 4);
    a[0] = fmaf(s, bf_lo(m.v[k].x), a[0]); a[1] = fmaf(s, bf_hi(m.v[k].x), a[1]);
    a[2] = fmaf(s, bf_lo(m.v[k].y), a[2]); a[3] = fmaf(s, bf_hi(m.v[k].y), a[3]);
    a[4] = fmaf(s, bf_lo(m.v[k].z), a[4]); a[5] = fmaf(s, bf_hi(m.v[k].z), a[5]);
    a[6] = fmaf(s, bf_lo(m.v[k].w), a[6]); a[7] = fmaf(s, bf_hi(m.v[k].w), a[7]);
  }
  bar_sync(BAR_CONS, 256);
  if (tid < 252) {
    sts4f(sb + OFF_AUXR + (rg * 56 + ch * 8) * 4, a[0], a[1], a[2], a[3]);
    sts4f(sb + OFF_AUXR + (rg * 56 + ch * 8 + 4) * 4, a[4], a[5], a[6], a[7]);
  }
  bar_sync(BAR_CONS, 256);
  if (tid < 224) {
    const int cc = tid >> 2, part = tid & 3;
    float s = 0.f;
#pragma unroll
    for (int k = 0; k < 9; k++) s += ldsf(sb + OFF_AUXR + ((part * 9 + k) * 56 + cc) * 4);
    s += __shfl_xor_sync(0xffffffffu, s, 1);
    s += __shfl_xor_sync(0xffffffffu, s, 2);
    if (part == 0) st_rlx2(&g_modw[col0 + cc], __float_as_uint(round_bf16(s)), ep);
  }
}

__global__ void __cluster_dims__(2, 1, 1) __launch_bounds__(NTHREADS, 1)
fused_block_kernel(const __grid_constant__ CUtensorMap tm_wsp, const __grid_constant__ CUtensorMap tm_wout, const Params p) {
  extern __shared__ __align__(1024) unsigned char smem_raw[];
  const uint32_t sb = s2u(smem_raw);
  const int tid = threadIdx.x, lane = tid & 31;
  const int warp = __shfl_sync(0xffffffffu, tid >> 5, 0);
  const int bid = blockIdx.x;
  const uint32_t rank = bid & 1;
  const int cl = bid >> 1;
  const int ti = cl & 15, tj = (cl >> 4) * 2 + (int)rank;
  const bool is_conv = bid < NCONV;
  const uint32_t fullA = sb + OFF_BAR, emptyA = fullA + 8 * NA, fullB = emptyA + 8 * NA, emptyB = fullB + 8 * NB;
  const uint32_t ep = g_epoch[bid] + 1;
  TS(0);
  if (tid == 0) {
    if (sb & 1023) __trap();
    for (int s = 0; s < NA; s++) { mbar_init(fullA + 8 * s, 1); mbar_init(emptyA + 8 * s, 4); }
    for (int s = 0; s < NB; s++) { mbar_init(fullB + 8 * s, 1); mbar_init(emptyB + 8 * s, 2); }
    asm volatile("fence.mbarrier_init.release.cluster;" ::: "memory");
  }
  asm volatile("barrier.cluster.arrive.relaxed.aligned;" ::: "memory");

  if (warp >= 8) {
    asm volatile("setmaxnreg.dec.sync.aligned.u32 104;");
    const int tw = tid - 256;
    if (is_conv) {
      const GenParams g2 = load_gen_params(p, 4 * bid + 2, tw), g3 = load_gen_params(p, 4 * bid + 3, tw);
      asm volatile("barrier.cluster.wait.aligned;" ::: "memory");
      gen_kernel(g2, sb + OFF_GEN2, sb + OFF_KTAB + 2 * KTAB_CH, tw, BAR_WG2);
      bar_arrive(BAR_K2, 256);
      if (warp == 10 && elect()) {
#pragma unroll
        for (int u = 0; u < 4; u++) prefetch_l2(p.w_sp + (size_t)bid * 32768 + u * 8192, 16384);
        prefetch_l2(p.w_out + (size_t)bid * 3136, 6272);
      }
      bar_sync(BAR_WG2, 128);
      gen_kernel(g3, sb + OFF_GEN2, sb + OFF_KTAB + 3 * KTAB_CH, tw, BAR_WG2);
      bar_arrive(BAR_K3, 256);
      bar_sync(BAR_WG2, 128);
      TS(16);
    } else {
      asm volatile("barrier.cluster.wait.aligned;" ::: "memory");
      bar_sync(BAR_AUX, 384);
      if (warp == 10 && elect()) {
#pragma unroll
        for (int u = 0; u < 4; u++) prefetch_l2(p.w_sp + (size_t)bid * 32768 + u * 8192, 16384);
        prefetch_l2(p.w_out + (size_t)bid * 3136, 6272);
      }
    }
    if (warp == 8) {
      if (elect()) {
        int slot = 0; uint32_t ph = 0;
        for (int kb = 0; kb < 7; kb++) {
          mbar_wait(emptyA + 8 * kb, 0);
          wait_flag(&g_cnt_x1[kb * 32], ep * 64u);
          fence_async_all();
          mbar_expect(fullA + 8 * kb, 16384);
          bulk_g2s_mc(sb + OFF_A + kb * A_SLOT + rank * 8192, (const char*)g_x1 + (size_t)(ti * 7 + kb) * 16384 + rank * 8192, 8192, fullA + 8 * kb);
        }
        ph = 1;
        for (int kk = 0; kk < 32; kk++) {
          mbar_wait(emptyA + 8 * slot, ph);
          mbar_expect(fullA + 8 * slot, 16384);
          tma2d_mc(sb + OFF_A + slot * A_SLOT + rank * 8192, &tm_wsp, kk * 64, ti * 128 + (int)rank * 64, fullA + 8 * slot);
          if (++slot == NA) { slot = 0; ph ^= 1; }
        }
        for (int jj = 0; jj < 8; jj++) {
          const char* src = (const char*)g_gt + ((size_t)(ti * 8 + jj) * 2 + rank) * 14336;
          mbar_wait(emptyA + 8 * slot, ph);
          wait_flag(&g_flag_gt[((ti * 8 + jj) * 2 + rank) * 8], ep);
          fence_async_all();
          mbar_expect(fullA + 8 * slot, 16384);
          bulk_g2s_mc(sb + OFF_A + slot * A_SLOT + rank * 8192, src, 8192, fullA + 8 * slot);
          if (++slot == NA) { slot = 0; ph ^= 1; }
          mbar_wait(emptyA + 8 * slot, ph);
          mbar_expect(fullA + 8 * slot, 12288);
          bulk_g2s_mc(sb + OFF_A + slot * A_SLOT + rank * 8192, src + 8192, 6144, fullA + 8 * slot);
          if (++slot == NA) { slot = 0; ph ^= 1; }
        }
      }
    } else if (warp == 9) {
      if (elect()) {
        int slot = 0; uint32_t ph = 1;
        for (int b = 0; b < 14; b++) {
          const int blk = (b >= 7 ? 8 : 0) + tj, kb = b >= 7 ? b - 7 : b;
          mbar_wait(emptyB + 8 * slot, ph);
          if (kb == 0) { wait_flag(&g_flag_wp[blk * 8], ep); fence_async_all(); }
          mbar_expect(fullB + 8 * slot, B_SLOT);
          bulk_g2s(sb + OFF_B + slot * B_SLOT, (const char*)g_wp + (size_t)(blk * 7 + kb) * B_SLOT, B_SLOT, fullB + 8 * slot);
          if (++slot == NB) { slot = 0; ph ^= 1; }
        }
        for (int kk = 0; kk < 32; kk++) {
          mbar_wait(emptyB + 8 * slot, ph);
          wait_flag(&g_flag_z2[(tj * 32 + kk) * 8], ep);
          fence_async_all();
          mbar_expect(fullB + 8 * slot, B_SLOT);
          bulk_g2s(sb + OFF_B + slot * B_SLOT, (const char*)g_z2 + (size_t)(tj * 32 + kk) * B_SLOT, B_SLOT, fullB + 8 * slot);
          if (++slot == NB) { slot = 0; ph ^= 1; }
        }
        for (int jj = 0; jj < 8; jj++) {
          mbar_wait(emptyB + 8 * slot, ph);
          mbar_expect(fullB + 8 * slot, B_SLOT);
          tma2d(sb + OFF_B + slot * B_SLOT, &tm_wout, tj * 56, jj * 112, fullB + 8 * slot);
          if (++slot == NB) { slot = 0; ph ^= 1; }
        }
      }
    }
    __syncwarp();
    asm volatile("barrier.cluster.arrive.aligned;" ::: "memory");
    asm volatile("barrier.cluster.wait.aligned;" ::: "memory");
  } else {
    asm volatile("setmaxnreg.inc.sync.aligned.u32 200;");
    const int wg = warp >> 2, tw = tid & 127, wp = warp & 3, g = lane >> 2, c = lane & 3;
    uint32_t rv[2][7];
    {
      const uint32_t* xr = (const uint32_t*)(p.x + (size_t)(16 * bid + 2 * warp) * DM) + lane;
#pragma unroll
      for (int r = 0; r < 2; r++)
#pragma unroll
        for (int k = 0; k < 7; k++) rv[r][k] = __ldg(xr + r * (DM / 2) + 32 * k);
    }
    if (is_conv) {
      const GenParams gp = load_gen_params(p, 4 * bid + wg, tw);
      uint2 xc[8];
#pragma unroll
      for (int e = 0; e < 8; e++) xc[e] = __ldg((const uint2*)(p.x + (size_t)(8 * tid + e) * DM + 4 * bid));
      const uint2 dsk = __ldg((const uint2*)(p.dskip + 4 * bid));
      ln1_stats(rv, 16 * bid + 2 * warp, lane, ep);
      TS(1 + wg);
      asm volatile("barrier.cluster.wait.aligned;" ::: "memory");
      gen_kernel(gp, sb + OFF_GEN01 + wg * 4 * GEN_BYTES, sb + OFF_KTAB + wg * KTAB_CH, tw, BAR_WG0 + wg);
      if (tid < 64) sts128(sb + OFF_H + (tid >> 4) * H_CH + ((tid >> 3) & 1) * H_HI + (tid & 7) * 16, 0, 0, 0, 0);
      TS(3 + wg);
      {
        uint4 st[4];
        unsigned it = 0;
        bool ok;
        do {
#pragma unroll
          for (int u = 0; u < 4; u++) st[u] = ld_rlx4((const uint4*)&g_st1[8 * tid] + u);
          ok = true;
#pragma unroll
          for (int u = 0; u < 4; u++) ok = ok && st[u].y == ep && st[u].w == ep;
        } while (!ok && ++it < SPIN_LIMIT);
        uint32_t ca1[4], sa2[4];
#pragma unroll
        for (int q = 0; q < 4; q++) {
          sa2[q] = dup_bf16(wait_modw(&g_modw[4 * bid + q], ep));
          ca1[q] = dup_bf16(1.f + wait_modw(&g_modw[DM + 4 * bid + q], ep));
        }
        float n[8][4];
#pragma unroll
        for (int e = 0; e < 8; e++) {
          const uint32_t w = (e & 1) ? st[e >> 1].z : st[e >> 1].x;
          const uint32_t m2 = __byte_perm(w, w, 0x1010);
          const float rs = __frcp_rn(bf_hi(w));
          const uint32_t d01 = bf2_sub(xc[e].x, m2), d23 = bf2_sub(xc[e].y, m2);
          n[e][0] = bf_lo(d01) * rs; n[e][1] = bf_hi(d01) * rs; n[e][2] = bf_lo(d23) * rs; n[e][3] = bf_hi(d23) * rs;
        }
#pragma unroll
        for (int q = 0; q < 4; q++) {
          uint32_t hv[4], xv[4];
#pragma unroll
          for (int u = 0; u < 4; u++) {
            hv[u] = bf2_add(bf2_mul(pack_bf16(n[2 * u][q], n[2 * u + 1][q]), ca1[q]), sa2[q]);
            const uint32_t a = (q < 2) ? xc[2 * u].x : xc[2 * u].y, b = (q < 2) ? xc[2 * u + 1].x : xc[2 * u + 1].y;
            xv[u] = __byte_perm(a, b, (q & 1) ? 0x7632 : 0x5410);
          }
          sts128(sb + OFF_H + q * H_CH + (tid & 1) * H_HI + (8 + (tid >> 1)) * 16, hv[0], hv[1], hv[2], hv[3]);
          sts128(sb + OFF_X + q * 4096 + (tid & 1) * 2048 + (tid >> 1) * 16, xv[0], xv[1], xv[2], xv[3]);
        }
      }
      fence_async_smem();
      bar_sync(BAR_CONS, 256);
      if (tw < 6) mbar_arrive_cluster(emptyA + 8 * (tw >> 1), tw & 1);
      TS(5 + wg);
      const uint32_t dk_a = wg ? __byte_perm(dsk.x, 0, 0x3232) : __byte_perm(dsk.x, 0, 0x1010);
      const uint32_t dk_b = wg ? __byte_perm(dsk.y, 0, 0x3232) : __byte_perm(dsk.y, 0, 0x1010);
      const uint32_t ga_a = dup_bf16(wait_modw(&g_modw[2 * DM + 4 * bid + wg], ep));
      const uint32_t ga_b = dup_bf16(wait_modw(&g_modw[2 * DM + 4 * bid + 2 + wg], ep));
      conv_channel(sb, wg, bid, tw, wg, 0, dk_a, ga_a);
      TS(7 + wg);
      bar_sync(BAR_K2 + wg, 256);
      conv_channel(sb, 2 + wg, bid, tw, wg, 1, dk_b, ga_b);
      bar_sync(BAR_CONS, 256);
      if (tw < 8) mbar_arrive_cluster(emptyA + 8 * (3 + (tw >> 1)), tw & 1);
      TS(9 + wg);
    } else {
      const int a = bid - NCONV;
      const int wcol = (a < 8 ? FH : 0) + 112 * (a & 7);
      for (int u = tid; u < DM * 14; u += 256) {
        const int r = u / 14, cc = u - r * 14;
        asm volatile("cp.async.cg.shared.global [%0], [%1], 16;" ::"r"(sb + OFF_WIN + r * 224 + cc * 16), "l"(p.w_in + (size_t)r * FF + wcol + cc * 8) : "memory");
      }
      asm volatile("cp.async.commit_group;" ::: "memory");
      ModLoads m1, m2;
      const int c1 = 56 * a, c2 = 3 * DM + 56 * a, c3 = (a < 8 ? 2 * DM : 5 * DM) + 56 * (a & 7);
      mod_load(m1, p, c1, tid);
      for (int u = tid; u < DM; u += 256) { const float cv = ldg_bf16(p.cvec + u); stsf(sb + OFF_AUXS + u * 4, round_bf16(cv / (1.f + __expf(-cv)))); }
      mod_load(m2, p, c2, tid);
      ln1_stats(rv, 16 * bid + 2 * warp, lane, ep);
      asm volatile("barrier.cluster.wait.aligned;" ::: "memory");
      bar_sync(BAR_CONS, 256);
      mod_finish(m1, sb, c1, tid, ep);
      TS(1 + wg);
      mod_load(m1, p, c3, tid);
      mod_finish(m2, sb, c2, tid, ep);
      mod_finish(m1, sb, c3, tid, ep);
      TS(3 + wg);
      for (int u = tid; u < 2 * DM; u += 256) {
        const float v = wait_modw(&g_modw[3 * DM + u], ep);
        if (u < DM) stsf(sb + OFF_AUXS + (2 * DM + u) * 4, v); else stsf(sb + OFF_AUXS + u * 4, round_bf16(1.f + v));
      }
      asm volatile("cp.async.wait_group 0;" ::: "memory");
      bar_sync(BAR_CONS, 256);
      if (tid < 224) {
        const int n2 = tid % 56, q = tid / 56;
        float cs0 = 0.f, cs1 = 0.f, bi0 = 0.f, bi1 = 0.f;
#pragma unroll 2
        for (int c8 = 0; c8 < 14; c8++) {
          float w0[8], w1[8];
#pragma unroll
          for (int e = 0; e < 8; e++) {
            const int d = 4 * (8 * c8 + e) + q;
            const uint32_t w = lds32(sb + OFF_WIN + d * 224 + n2 * 4);
            const float s1 = ldsf(sb + OFF_AUXS + (DM + d) * 4), s0 = ldsf(sb + OFF_AUXS + (2 * DM + d) * 4);
            bi0 = fmaf(s0, bf_lo(w), bi0); bi1 = fmaf(s0, bf_hi(w), bi1);
            const uint32_t wpk = pack_bf16(s1 * bf_lo(w), s1 * bf_hi(w));
            w0[e] = bf_lo(wpk); w1[e] = bf_hi(wpk);
            cs0 += w0[e]; cs1 += w1[e];
          }
          const int k = q * NCONV + 8 * c8;
          uint4* dst = &g_wp[(a * 7 + (k >> 6)) * 896 + ((k & 63) >> 3) * 112 + 2 * n2];
          dst[0] = make_uint4(pack_bf16(w0[0], w0[1]), pack_bf16(w0[2], w0[3]), pack_bf16(w0[4], w0[5]), pack_bf16(w0[6], w0[7]));
          dst[1] = make_uint4(pack_bf16(w1[0], w1[1]), pack_bf16(w1[2], w1[3]), pack_bf16(w1[4], w1[5]), pack_bf16(w1[6], w1[7]));
        }
        sts4f(sb + OFF_AUXR + (q * 56 + n2) * 16, cs0, bi0, cs1, bi1);
      }
      bar_sync(BAR_CONS, 256);
      if (tid < 56) {
        float4 s = lds4f(sb + OFF_AUXR + tid * 16);
#pragma unroll
        for (int q = 1; q < 4; q++) { const float4 t = lds4f(sb + OFF_AUXR + (q * 56 + tid) * 16); s.x += t.x; s.y += t.y; s.z += t.z; s.w += t.w; }
        *(float4*)&g_csb[a * 112 + 2 * tid] = s;
      }
      fence_async_all();
      bar_sync(BAR_CONS, 256);
      if (tid == 0) { fence_gpu(); st_rel(&g_flag_wp[a * 8], ep); }
      bar_arrive(BAR_AUX, 384);
      if (tw < 14) mbar_arrive_cluster(emptyA + 8 * (tw >> 1), tw & 1);
      TS(9 + wg);
    }

    float acc2[56], acc1[56];
    float sum[8], sq[8];
#pragma unroll
    for (int e = 0; e < 8; e++) { sum[e] = 0.f; sq[e] = 0.f; }
    int bs = 0; uint32_t bph = 0;
    int prevb = -1;
    const uint32_t stat_off = wg * 8192 + (tw >> 3) * 128 + (((tw & 7) ^ ((tw >> 3) & 7)) * 16);
#pragma unroll 1
    for (int kb = 0; kb < 7; kb++) {
      mbar_wait(fullA + 8 * kb, 0);
      mbar_wait(fullB + 8 * bs, bph);
      const uint64_t da = desc_sw128(sb + OFF_A + kb * A_SLOT + wg * 8192), db = desc_nosw(sb + OFF_B + bs * B_SLOT, 1792, 128);
      wg_fence();
#pragma unroll
      for (int k = 0; k < 4; k++) wgmma_n112_tA(acc2, da + 128 * k, db + 224 * k, (kb | k) != 0);
      wg_commit();
#pragma unroll
      for (int e = 0; e < 4; e++) {
        const uint4 v = lds128(sb + OFF_A + kb * A_SLOT + stat_off + e * 2048);
        const uint32_t w[4] = {v.x, v.y, v.z, v.w};
#pragma unroll
        for (int u = 0; u < 4; u++) {
          const float lo = bf_lo(w[u]), hi = bf_hi(w[u]);
          sum[2 * u] += lo; sq[2 * u] = fmaf(lo, lo, sq[2 * u]);
          sum[2 * u + 1] += hi; sq[2 * u + 1] = fmaf(hi, hi, sq[2 * u + 1]);
        }
      }
      wg_wait<1>();
      if (prevb >= 0 && tw == 0) mbar_arrive(emptyB + 8 * prevb);
      prevb = bs;
      if (++bs == NB) { bs = 0; bph ^= 1; }
    }
    TS(11 + wg);
#pragma unroll 1
    for (int kb = 0; kb < 7; kb++) {
      mbar_wait(fullB + 8 * bs, bph);
      const uint64_t da = desc_sw128(sb + OFF_A + kb * A_SLOT + wg * 8192), db = desc_nosw(sb + OFF_B + bs * B_SLOT, 1792, 128);
      wg_fence();
#pragma unroll
      for (int k = 0; k < 4; k++) wgmma_n112_tA(acc1, da + 128 * k, db + 224 * k, (kb | k) != 0);
      wg_commit();
      wg_wait<1>();
      if (tw == 0) mbar_arrive(emptyB + 8 * prevb);
      prevb = bs;
      if (++bs == NB) { bs = 0; bph ^= 1; }
    }
    uint32_t xres[14];
    {
      const int tl = 16 * wp + g;
#pragma unroll
      for (int n = 0; n < 7; n++) {
#pragma unroll
        for (int hf = 0; hf < 2; hf++) {
          uint32_t v[2];
#pragma unroll
          for (int e = 0; e < 2; e++) {
            const int d = 56 * tj + 8 * n + 2 * c + e;
            const int k = (d & 3) * NCONV + (d >> 2);
            const int t = tl + 8 * hf;
            v[e] = lds16(sb + OFF_A + (k >> 6) * A_SLOT + wg * 8192 + (k & 63) * 128 + (((t >> 3) ^ (k & 7)) * 16) + (t & 7) * 2);
          }
          xres[2 * n + hf] = v[0] | (v[1] << 16);
        }
      }
    }
#pragma unroll
    for (int e = 0; e < 8; e++) {
      sum[e] += __shfl_xor_sync(0xffffffffu, sum[e], 8); sum[e] += __shfl_xor_sync(0xffffffffu, sum[e], 16);
      sq[e] += __shfl_xor_sync(0xffffffffu, sq[e], 8); sq[e] += __shfl_xor_sync(0xffffffffu, sq[e], 16);
    }
    if (lane < 8) {
      const uint32_t o = sb + OFF_ST2 + ((wg * 4 + wp) * 64 + lane * 8) * 8;
      sts4f(o, sum[0], sq[0], sum[1], sq[1]); sts4f(o + 16, sum[2], sq[2], sum[3], sq[3]);
      sts4f(o + 32, sum[4], sq[4], sum[5], sq[5]); sts4f(o + 48, sum[6], sq[6], sum[7], sq[7]);
    }
    if (tid < 224) {
      const int blk = (tid >= 112 ? 8 : 0) + tj;
      wait_flag(&g_flag_wp[blk * 8], ep);
      const float2 v = __ldcg(&g_csb[blk * 112 + (tid >= 112 ? tid - 112 : tid)]);
      sts2f(sb + OFF_CSB + tid * 8, v.x, v.y);
    } else if (tid < 252) {
      const int u = tid - 224;
      const float g0 = wait_modw(&g_modw[5 * DM + 56 * tj + 2 * u], ep), g1 = wait_modw(&g_modw[5 * DM + 56 * tj + 2 * u + 1], ep);
      sts32(sb + OFF_GB + u * 4, pack_bf16(g0, g1));
    }
    wg_wait<0>();
    if (tw == 0) mbar_arrive(emptyB + 8 * prevb);
    bar_sync(BAR_CONS, 256);
    if (tw < 14) mbar_arrive_cluster(emptyA + 8 * (tw >> 1), tw & 1);
    TS(13 + wg);
    float ra[2], rb[2];
#pragma unroll
    for (int hf = 0; hf < 2; hf++) {
      float s = 0.f, q = 0.f;
#pragma unroll
      for (int w = 0; w < 4; w++) { const float2 v = lds2f(sb + OFF_ST2 + ((wg * 4 + w) * 64 + 16 * wp + g + 8 * hf) * 8); s += v.x; q += v.y; }
      const float mean = s * (1.f / DM);
      const float var = fmaxf(q * (1.f / DM) - mean * mean, 0.f);
      ra[hf] = rsqrtf(var + 1e-5f); rb[hf] = -ra[hf] * mean;
    }
    {
      float s0 = 0.f, q0 = 0.f, s1 = 0.f, q1 = 0.f;
#pragma unroll
      for (int n = 0; n < 14; n++) {
        const float4 cb = lds4f(sb + OFF_CSB + (8 * n + 2 * c) * 8);
        float* a = acc2 + 4 * n;
        a[0] = gelu_tanh(fmaf(ra[0], a[0], fmaf(rb[0], cb.x, cb.y))); a[1] = gelu_tanh(fmaf(ra[0], a[1], fmaf(rb[0], cb.z, cb.w)));
        a[2] = gelu_tanh(fmaf(ra[1], a[2], fmaf(rb[1], cb.x, cb.y))); a[3] = gelu_tanh(fmaf(ra[1], a[3], fmaf(rb[1], cb.z, cb.w)));
        s0 += a[0] + a[1]; q0 = fmaf(a[0], a[0], fmaf(a[1], a[1], q0));
        s1 += a[2] + a[3]; q1 = fmaf(a[2], a[2], fmaf(a[3], a[3], q1));
      }
#pragma unroll
      for (int o = 1; o < 4; o <<= 1) {
        s0 += __shfl_xor_sync(0xffffffffu, s0, o); q0 += __shfl_xor_sync(0xffffffffu, q0, o);
        s1 += __shfl_xor_sync(0xffffffffu, s1, o); q1 += __shfl_xor_sync(0xffffffffu, q1, o);
      }
      const int row = 64 * wg + 16 * wp + g;
      if (c < 2) st_rlx4(&g_st3[(ti * 8 + tj) * 128 + row + 8 * c], __float_as_uint(c ? s1 : s0), ep, __float_as_uint(c ? q1 : q0), ep);
#pragma unroll
      for (int n = 0; n < 14; n++) {
        const float4 cb = lds4f(sb + OFF_CSB + (112 + 8 * n + 2 * c) * 8);
        float* a = acc1 + 4 * n;
        a[0] = gelu_tanh(fmaf(ra[0], a[0], fmaf(rb[0], cb.x, cb.y))); a[1] = gelu_tanh(fmaf(ra[0], a[1], fmaf(rb[0], cb.z, cb.w)));
        a[2] = gelu_tanh(fmaf(ra[1], a[2], fmaf(rb[1], cb.x, cb.y))); a[3] = gelu_tanh(fmaf(ra[1], a[3], fmaf(rb[1], cb.z, cb.w)));
      }
      uint4 st[4];
      unsigned it = 0;
      bool ok;
      do {
#pragma unroll
        for (int u = 0; u < 4; u++) st[u] = ld_rlx4(&g_st3[(ti * 8 + c + 4 * (u & 1)) * 128 + row + 8 * (u >> 1)]);
        ok = true;
#pragma unroll
        for (int u = 0; u < 4; u++) ok = ok && st[u].y == ep && st[u].w == ep;
      } while (!ok && ++it < SPIN_LIMIT);
      s0 = __uint_as_float(st[0].x) + __uint_as_float(st[1].x); q0 = __uint_as_float(st[0].z) + __uint_as_float(st[1].z);
      s1 = __uint_as_float(st[2].x) + __uint_as_float(st[3].x); q1 = __uint_as_float(st[2].z) + __uint_as_float(st[3].z);
#pragma unroll
      for (int o = 1; o < 4; o <<= 1) {
        s0 += __shfl_xor_sync(0xffffffffu, s0, o); q0 += __shfl_xor_sync(0xffffffffu, q0, o);
        s1 += __shfl_xor_sync(0xffffffffu, s1, o); q1 += __shfl_xor_sync(0xffffffffu, q1, o);
      }
      const float m0 = s0 * (1.f / FH), m1 = s1 * (1.f / FH);
      const float r0 = rsqrtf(fmaxf(q0 * (1.f / FH) - m0 * m0, 0.f) + 1e-5f), r1 = rsqrtf(fmaxf(q1 * (1.f / FH) - m1 * m1, 0.f) + 1e-5f);
      const float o0 = -m0 * r0, o1 = -m1 * r1;
      const uint32_t sa = sb + OFF_STG + wg * B_SLOT + (2 * wp + ((lane >> 3) & 1)) * 1792 + ((lane & 7) + (lane >> 4) * 8) * 16;
#pragma unroll
      for (int n = 0; n < 14; n += 2) {
        const float* a = acc2 + 4 * n;
        stsm4t(sa + n * 128, pack_bf16(fmaf(a[0], r0, o0), fmaf(a[1], r0, o0)), pack_bf16(fmaf(a[2], r1, o1), fmaf(a[3], r1, o1)),
               pack_bf16(fmaf(a[4], r0, o0), fmaf(a[5], r0, o0)), pack_bf16(fmaf(a[6], r1, o1), fmaf(a[7], r1, o1)));
      }
      fence_async_smem();
      bar_sync(BAR_WG0 + wg, 128);
      if (tw == 0) {
        bulk_s2g((char*)g_z2 + (size_t)(tj * 32 + 2 * ti + wg) * B_SLOT, sb + OFF_STG + wg * B_SLOT, B_SLOT);
        fence_gpu();
        st_rel(&g_flag_z2[(tj * 32 + 2 * ti + wg) * 8], ep);
      }
    }
    uint32_t z1[28];
#pragma unroll
    for (int n = 0; n < 28; n++) z1[n] = pack_bf16(acc1[2 * n], acc1[2 * n + 1]);
    const uint32_t bsp0 = dup_bf16(ldg_bf16(p.b_sp + ti * 128 + 64 * wg + 16 * wp + g)), bsp1 = dup_bf16(ldg_bf16(p.b_sp + ti * 128 + 64 * wg + 16 * wp + g + 8));
    TS(17 + wg);

    int as = 0; uint32_t aph = 1;
    int preva = -1; prevb = -1;
#pragma unroll 1
    for (int kk = 0; kk < 32; kk++) {
      mbar_wait(fullA + 8 * as, aph);
      mbar_wait(fullB + 8 * bs, bph);
      if (kk == 0) TS(19 + wg);
      const uint64_t da = desc_sw128(sb + OFF_A + as * A_SLOT + wg * 8192), db = desc_nosw(sb + OFF_B + bs * B_SLOT, 1792, 128);
      wg_fence();
#pragma unroll
      for (int k = 0; k < 4; k++) wgmma_n112(acc2, da + 2 * k, db + 224 * k, (kk | k) != 0);
      wg_commit();
      wg_wait<1>();
      if (preva >= 0) {
        if (tw < 2) mbar_arrive_cluster(emptyA + 8 * preva, tw);
        else if (tw == 32) mbar_arrive(emptyB + 8 * prevb);
      }
      preva = as; prevb = bs;
      if (++as == NA) { as = 0; aph ^= 1; }
      if (++bs == NB) { bs = 0; bph ^= 1; }
    }
    wg_wait<0>();
    if (tw < 2) mbar_arrive_cluster(emptyA + 8 * preva, tw);
    else if (tw == 32) mbar_arrive(emptyB + 8 * prevb);
    TS(21 + wg);
    {
      const uint32_t sa = sb + OFF_STG + wg * B_SLOT + (lane >> 4) * 1024 + (16 * wp + (lane & 7) + ((lane >> 3) & 1) * 8) * 16;
#pragma unroll
      for (int n = 0; n < 14; n += 2) {
        const float* a = acc2 + 4 * n;
        stsm4(sa + n * 1024, bf2_mul(z1[2 * n], bf2_add(pack_bf16(a[0], a[1]), bsp0)), bf2_mul(z1[2 * n + 1], bf2_add(pack_bf16(a[2], a[3]), bsp1)),
              bf2_mul(z1[2 * n + 2], bf2_add(pack_bf16(a[4], a[5]), bsp0)), bf2_mul(z1[2 * n + 3], bf2_add(pack_bf16(a[6], a[7]), bsp1)));
      }
      fence_async_smem();
      bar_sync(BAR_WG0 + wg, 128);
      if (tw == 0) {
        bulk_s2g((char*)g_gt + ((size_t)(ti * 8 + tj) * 2 + wg) * 14336, sb + OFF_STG + wg * B_SLOT, 14336);
        fence_gpu();
        st_rel(&g_flag_gt[((ti * 8 + tj) * 2 + wg) * 8], ep);
      }
    }
    TS(23 + wg);
    float acc3[28];
    {
      int pa0 = -1, pa1 = -1; prevb = -1;
#pragma unroll 1
      for (int jj = 0; jj < 8; jj++) {
        mbar_wait(fullB + 8 * bs, bph);
        mbar_wait(fullA + 8 * as, aph);
        if (jj == 0) TS(25 + wg);
        const uint64_t db = desc_sw128(sb + OFF_B + bs * B_SLOT);
        const int a0 = as;
        const uint64_t da0 = desc_nosw(sb + OFF_A + as * A_SLOT + wg * 8192, 1024, 128);
        wg_fence();
#pragma unroll
        for (int k = 0; k < 4; k++) wgmma_n56_tB(acc3, da0 + 128 * k, db + 128 * k, (jj | k) != 0);
        if (++as == NA) { as = 0; aph ^= 1; }
        mbar_wait(fullA + 8 * as, aph);
        const uint64_t da1 = desc_nosw(sb + OFF_A + as * A_SLOT + wg * 8192, 1024, 128);
#pragma unroll
        for (int k = 0; k < 3; k++) wgmma_n56_tB(acc3, da1 + 128 * k, db + 128 * (4 + k), 1);
        wg_commit();
        wg_wait<1>();
        if (pa0 >= 0) {
          if (tw < 2) mbar_arrive_cluster(emptyA + 8 * pa0, tw);
          else if (tw < 4) mbar_arrive_cluster(emptyA + 8 * pa1, tw - 2);
          else if (tw == 32) mbar_arrive(emptyB + 8 * prevb);
        }
        pa0 = a0; pa1 = as; prevb = bs;
        if (++as == NA) { as = 0; aph ^= 1; }
        if (++bs == NB) { bs = 0; bph ^= 1; }
      }
      wg_wait<0>();
    }
    TS(27 + wg);
    {
      const uint32_t ob = sb + OFF_STG + warp * 2304;
      uint32_t o[14];
#pragma unroll
      for (int n = 0; n < 7; n++) {
        const uint32_t gb2 = lds32(sb + OFF_GB + (4 * n + c) * 4);
        o[2 * n] = bf2_add(xres[2 * n], bf2_mul(gb2, pack_bf16(acc3[4 * n], acc3[4 * n + 1])));
        o[2 * n + 1] = bf2_add(xres[2 * n + 1], bf2_mul(gb2, pack_bf16(acc3[4 * n + 2], acc3[4 * n + 3])));
      }
      bar_sync(BAR_CONS, 256);
      const uint32_t sa = ob + ((lane & 7) + ((lane >> 3) & 1) * 8) * 144 + (lane >> 4) * 16;
#pragma unroll
      for (int n = 0; n < 6; n += 2) stsm4(sa + n * 16, o[2 * n], o[2 * n + 1], o[2 * n + 2], o[2 * n + 3]);
      stsm2(ob + ((lane & 7) + ((lane >> 3) & 1) * 8) * 144 + 96, o[12], o[13]);
      __syncwarp();
#pragma unroll
      for (int u = 0; u < 4; u++) {
        const int idx = lane + 32 * u;
        if (idx < 112) {
          const int r = idx / 7, cc = idx - r * 7;
          const uint4 v = lds128(ob + r * 144 + cc * 16);
          *(uint4*)(p.out + (size_t)(ti * 128 + 16 * warp + r) * DM + 56 * tj + cc * 8) = v;
        }
      }
    }
    if (tid == 0) g_epoch[bid] = ep;
    TS(29 + wg);
    asm volatile("barrier.cluster.arrive.aligned;" ::: "memory");
    asm volatile("barrier.cluster.wait.aligned;" ::: "memory");
  }
}

typedef CUresult (*EncodeFn)(CUtensorMap*, CUtensorMapDataType, cuuint32_t, void*, const cuuint64_t*, const cuuint64_t*, const cuuint32_t*,
                             const cuuint32_t*, CUtensorMapInterleave, CUtensorMapSwizzle, CUtensorMapL2promotion, CUtensorMapFloatOOBfill);

}

extern "C" void kernel_launch(void* const* d_in, const int* in_sizes, int n_in, void* d_out, int out_size) {
  (void)in_sizes; (void)n_in; (void)out_size;
  static EncodeFn enc = nullptr;
  if (!enc) {
    void* fn = nullptr;
    cudaDriverEntryPointQueryResult qr;
    cudaGetDriverEntryPoint("cuTensorMapEncodeTiled", &fn, cudaEnableDefault, &qr);
    enc = (EncodeFn)fn;
    cudaFuncSetAttribute(fused_block_kernel, cudaFuncAttributeMaxDynamicSharedMemorySize, SMEM_BYTES);
  }
  Params p;
  p.x = (const __nv_bfloat16*)d_in[0];
  p.a_re = (const __nv_bfloat16*)d_in[1]; p.a_im = (const __nv_bfloat16*)d_in[2];
  p.b_re = (const __nv_bfloat16*)d_in[3]; p.b_im = (const __nv_bfloat16*)d_in[4];
  p.c_re = (const __nv_bfloat16*)d_in[5]; p.c_im = (const __nv_bfloat16*)d_in[6];
  p.log_dt = (const __nv_bfloat16*)d_in[7]; p.dskip = (const __nv_bfloat16*)d_in[8];
  p.w_in = (const __nv_bfloat16*)d_in[10]; p.w_sp = (const __nv_bfloat16*)d_in[11];
  p.b_sp = (const __nv_bfloat16*)d_in[12]; p.w_out = (const __nv_bfloat16*)d_in[13];
  p.cvec = (const __nv_bfloat16*)d_in[14]; p.w_mod = (const __nv_bfloat16*)d_in[15];
  p.out = (__nv_bfloat16*)d_out;
  CUtensorMap tm_wsp, tm_wout;
  {
    cuuint64_t gd[2] = {SEQ, SEQ}, gs[1] = {SEQ * 2};
    cuuint32_t box[2] = {64, 64}, es[2] = {1, 1};
    enc(&tm_wsp, CU_TENSOR_MAP_DATA_TYPE_BFLOAT16, 2, d_in[11], gd, gs, box, es, CU_TENSOR_MAP_INTERLEAVE_NONE, CU_TENSOR_MAP_SWIZZLE_128B,
        CU_TENSOR_MAP_L2_PROMOTION_L2_128B, CU_TENSOR_MAP_FLOAT_OOB_FILL_NONE);
  }
  {
    cuuint64_t gd[2] = {DM, FH}, gs[1] = {DM * 2};
    cuuint32_t box[2] = {64, 112}, es[2] = {1, 1};
    enc(&tm_wout, CU_TENSOR_MAP_DATA_TYPE_BFLOAT16, 2, d_in[13], gd, gs, box, es, CU_TENSOR_MAP_INTERLEAVE_NONE, CU_TENSOR_MAP_SWIZZLE_128B,
        CU_TENSOR_MAP_L2_PROMOTION_L2_128B, CU_TENSOR_MAP_FLOAT_OOB_FILL_NONE);
  }
  fused_block_kernel<<<NCTA, NTHREADS, SMEM_BYTES>>>(tm_wsp, tm_wout, p);
}
```

```cpp
#include <cuda_runtime.h>
#include <cuda.h>
#include <cuda_bf16.h>
#include <cuda_fp16.h>
#include <stdint.h>

namespace {

constexpr int SEQ = 2048, DM = 448, NMODE = 256, FF = 1792, FH = 896;
constexpr int NCTA = 128, NCONV = 112, NTHREADS = 384;
constexpr int NA = 7, NB = 5, NB2 = 7;
constexpr uint32_t A_SLOT = 16384, B_SLOT = 14336;
constexpr uint32_t OFF_A = 0;
constexpr uint32_t OFF_B = OFF_A + NA * A_SLOT;
constexpr uint32_t OFF_STG = OFF_B + NB * B_SLOT;
constexpr uint32_t OFF_MISC = OFF_STG + 28672;
constexpr uint32_t SMEM_BYTES = 232448;
constexpr uint32_t GEN_PITCH = 272, GEN_Q = 21 * GEN_PITCH, GEN_QP = 512, GEN_BYTES = GEN_Q + 8 * GEN_QP + 256;
constexpr uint32_t OFF_GEN01 = 0;
constexpr uint32_t OFF_GEN2 = OFF_B;
constexpr uint32_t OFF_RED = 32768;
constexpr uint32_t KTAB_CH = 2080 * 4, KTAB_ODD = 1040 * 4;
constexpr uint32_t OFF_KTAB = OFF_B - 4 * KTAB_CH;
constexpr uint32_t H_HI = 2240, H_CH = 4480;
constexpr uint32_t OFF_H = OFF_STG;
constexpr uint32_t OFF_TR = OFF_STG;
constexpr uint32_t X_CH = 4096;
constexpr uint32_t OFF_X = OFF_MISC + 1024;
constexpr uint32_t OFF_BAR = OFF_MISC;
constexpr uint32_t OFF_PUB = OFF_BAR + 384;
constexpr uint32_t OFF_T0 = OFF_MISC + 1024;
constexpr uint32_t OFF_CSB = OFF_T0;
constexpr uint32_t OFF_MODW = OFF_B + 40448;
constexpr uint32_t OFF_SCB = OFF_MODW + 21504;
constexpr uint32_t OFF_MODP = OFF_MODW + 22528;
constexpr uint32_t OFF_MODV = OFF_BAR + 512;
constexpr uint32_t OFF_LID = OFF_MODV + 128;
constexpr uint32_t OFF_WIN = 0;
constexpr uint32_t OFF_G1 = 100352;
constexpr uint32_t OFF_AUXR = 150528;
constexpr uint32_t OFF_AUXS = OFF_MISC + 1024;

constexpr int FS = 8;
constexpr unsigned SPIN_LIMIT = 1u << 22;

struct __align__(128) Scratch {
  uint4 nx[DM * SEQ / 4];
  uint4 wp[16 * 7 * 896];
  uint4 x1[16 * 7 * 1024];
  uint4 st3[16 * 8 * 128];
  uint4 z2[8 * 32 * 896];
  uint4 gt[16 * 8 * 1792];
  uint2 modw[6 * DM];
  uint4 csb[FF];
  uint32_t epoch[NCTA];
  uint32_t claim[64];
  uint32_t cnt_nx[32];
  uint32_t cnt_x1[128];
  uint32_t flag_wp[8 * 32];
  uint32_t flag_z2[256 * 8];
  uint32_t flag_gt[256 * 8];
};
__device__ Scratch g_scr;
__device__ __forceinline__ int fresh_tid();

struct Params {
  Scratch* s;
  uint32_t zero, pad;
  const __nv_bfloat16 *x, *a_re, *a_im, *b_re, *b_im, *c_re, *c_im, *log_dt, *cvec, *dskip, *w_sp, *b_sp, *w_out;
  __nv_bfloat16* out;
};

struct Maps { CUtensorMap wsp, wout, wmod, wmod8, win, nx, x1; };

__device__ __forceinline__ uint32_t s2u(const void* p) { return (uint32_t)__cvta_generic_to_shared(p); }
__device__ __forceinline__ void mbar_init(uint32_t b, uint32_t c) { asm volatile("mbarrier.init.shared::cta.b64 [%0], %1;" ::"r"(b), "r"(c)); }
__device__ __forceinline__ void mbar_expect(uint32_t b, uint32_t n) { asm volatile("mbarrier.arrive.expect_tx.shared::cta.b64 _, [%0], %1;" ::"r"(b), "r"(n) : "memory"); }
__device__ __forceinline__ void mbar_wait(uint32_t b, uint32_t ph) {
  asm volatile(
      "{.reg .pred p; .reg .u32 c; mov.u32 c, 0;\n"
      "LW: mbarrier.try_wait.parity.shared::cta.b64 p, [%0], %1; @p bra LD;\n"
      "add.u32 c, c, 1; setp.lt.u32 p, c, 4194304; @p bra LW;\n"
      "LD: }" ::"r"(b), "r"(ph) : "memory");
}
__device__ __forceinline__ void mbar_wait2(uint32_t b0, uint32_t ph0, uint32_t b1, uint32_t ph1) {
  asm volatile(
      "{.reg .pred p, q; .reg .u32 c; mov.u32 c, 0;\n"
      "LW: mbarrier.try_wait.parity.shared::cta.b64 p, [%0], %1; mbarrier.try_wait.parity.shared::cta.b64 q, [%2], %3; and.pred p, p, q; @p bra LD;\n"
      "add.u32 c, c, 1; setp.lt.u32 p, c, 4194304; @p bra LW;\n"
      "LD: }" ::"r"(b0), "r"(ph0), "r"(b1), "r"(ph1) : "memory");
}
__device__ __forceinline__ void mbar_arrive(uint32_t b) { asm volatile("mbarrier.arrive.shared::cta.b64 _, [%0];" ::"r"(b) : "memory"); }
__device__ __forceinline__ void mbar_arrive_cluster(uint32_t b, uint32_t cta) {
  asm volatile("{.reg .b32 r; mapa.shared::cluster.u32 r, %0, %1; mbarrier.arrive.shared::cluster.b64 _, [r];}" ::"r"(b), "r"(cta) : "memory");
}
__device__ __forceinline__ int fresh_tid() { int t; asm volatile("mov.u32 %0, %%tid.x;" : "=r"(t)); return t; }
__device__ __forceinline__ bool elect() { uint32_t e; asm volatile("{.reg .pred p; elect.sync _|p, 0xffffffff; selp.u32 %0,1,0,p;}" : "=r"(e)); return e != 0; }
__device__ __forceinline__ void bar_sync(int id, int n) { asm volatile("bar.sync %0, %1;" ::"r"(id), "r"(n) : "memory"); }
__device__ __forceinline__ void bar_arrive(int id, int n) { asm volatile("bar.arrive %0, %1;" ::"r"(id), "r"(n) : "memory"); }
__device__ __forceinline__ void fence_async_smem() { asm volatile("fence.proxy.async.shared::cta;" ::: "memory"); }
__device__ __forceinline__ void wg_fence() { asm volatile("wgmma.fence.sync.aligned;" ::: "memory"); }
__device__ __forceinline__ void wg_commit() { asm volatile("wgmma.commit_group.sync.aligned;" ::: "memory"); }
template <int N> __device__ __forceinline__ void wg_wait() { asm volatile("wgmma.wait_group.sync.aligned %0;" ::"n"(N) : "memory"); }

__device__ __forceinline__ void st_rlx(uint32_t* p, uint32_t v) { asm volatile("st.relaxed.gpu.global.u32 [%0], %1;" ::"l"(p), "r"(v) : "memory"); }
__device__ __forceinline__ void red_rlx(uint32_t* p, uint32_t v) { asm volatile("red.relaxed.gpu.global.add.u32 [%0], %1;" ::"l"(p), "r"(v) : "memory"); }
__device__ __forceinline__ uint32_t ld_rlx(const uint32_t* p) { uint32_t v; asm volatile("ld.relaxed.gpu.global.u32 %0, [%1];" : "=r"(v) : "l"(p) : "memory"); return v; }
__device__ __forceinline__ void gate_wait(const uint32_t* p, uint32_t target) {
  unsigned it = 0;
  while ((int)(ld_rlx(p) - target) < 0 && ++it < SPIN_LIMIT) __nanosleep(40);
}
__device__ __forceinline__ uint2 ld_rlx2(const uint2* p) { uint2 v; asm volatile("ld.relaxed.gpu.global.v2.u32 {%0,%1}, [%2];" : "=r"(v.x), "=r"(v.y) : "l"(p) : "memory"); return v; }
__device__ __forceinline__ uint4 ld_rlx4(const void* p) { uint4 v; asm volatile("ld.relaxed.gpu.global.v4.u32 {%0,%1,%2,%3}, [%4];" : "=r"(v.x), "=r"(v.y), "=r"(v.z), "=r"(v.w) : "l"(p) : "memory"); return v; }
__device__ __forceinline__ void st_rlx2(uint2* p, uint32_t a, uint32_t b) { asm volatile("st.relaxed.gpu.global.v2.u32 [%0], {%1,%2};" ::"l"(p), "r"(a), "r"(b) : "memory"); }
__device__ __forceinline__ void st_rlx4(uint4* p, uint32_t a, uint32_t b, uint32_t c, uint32_t d) { asm volatile("st.relaxed.gpu.global.v4.u32 [%0], {%1,%2,%3,%4};" ::"l"(p), "r"(a), "r"(b), "r"(c), "r"(d) : "memory"); }

__device__ __forceinline__ void bulk_g2s(uint32_t dst, const void* src, uint32_t bytes, uint32_t bar) {
  asm volatile("cp.async.bulk.shared::cluster.global.mbarrier::complete_tx::bytes [%0], [%1], %2, [%3];" ::"r"(dst), "l"(src), "r"(bytes), "r"(bar) : "memory");
}
__device__ __forceinline__ void bulk_g2s_mc(uint32_t dst, const void* src, uint32_t bytes, uint32_t bar) {
  asm volatile("cp.async.bulk.shared::cluster.global.mbarrier::complete_tx::bytes.multicast::cluster [%0], [%1], %2, [%3], %4;" ::"r"(dst), "l"(src), "r"(bytes), "r"(bar), "h"((uint16_t)3) : "memory");
}
__device__ __forceinline__ void tma2d(uint32_t dst, const CUtensorMap* tm, int c0, int c1, uint32_t bar) {
  asm volatile("cp.async.bulk.tensor.2d.shared::cluster.global.mbarrier::complete_tx::bytes [%0], [%1, {%3, %4}], [%2];" ::"r"(dst), "l"(tm), "r"(bar), "r"(c0), "r"(c1) : "memory");
}
__device__ __forceinline__ void tma2d_mc(uint32_t dst, const CUtensorMap* tm, int c0, int c1, uint32_t bar) {
  asm volatile("cp.async.bulk.tensor.2d.shared::cluster.global.mbarrier::complete_tx::bytes.multicast::cluster [%0], [%1, {%3, %4}], [%2], %5;" ::"r"(dst), "l"(tm), "r"(bar), "r"(c0), "r"(c1), "h"((uint16_t)3) : "memory");
}
__device__ __forceinline__ void stg128(void* p, uint4 v) { asm volatile("st.global.v4.u32 [%0], {%1,%2,%3,%4};" ::"l"(p), "r"(v.x), "r"(v.y), "r"(v.z), "r"(v.w) : "memory"); }
__device__ __forceinline__ void prefetch_l2(const void* p, uint32_t bytes) { asm volatile("cp.async.bulk.prefetch.L2.global [%0], %1;" ::"l"(p), "r"(bytes) : "memory"); }

__device__ __forceinline__ uint32_t lds32(uint32_t a) { uint32_t v; asm volatile("ld.shared.u32 %0, [%1];" : "=r"(v) : "r"(a)); return v; }
__device__ __forceinline__ float ldsf(uint32_t a) { float v; asm volatile("ld.shared.f32 %0, [%1];" : "=f"(v) : "r"(a)); return v; }
__device__ __forceinline__ float2 lds2f(uint32_t a) { float2 v; asm volatile("ld.shared.v2.f32 {%0,%1}, [%2];" : "=f"(v.x), "=f"(v.y) : "r"(a)); return v; }
__device__ __forceinline__ float4 lds4f(uint32_t a) { float4 v; asm volatile("ld.shared.v4.f32 {%0,%1,%2,%3}, [%4];" : "=f"(v.x), "=f"(v.y), "=f"(v.z), "=f"(v.w) : "r"(a)); return v; }
__device__ __forceinline__ uint4 lds128(uint32_t a) { uint4 v; asm volatile("ld.shared.v4.u32 {%0,%1,%2,%3}, [%4];" : "=r"(v.x), "=r"(v.y), "=r"(v.z), "=r"(v.w) : "r"(a)); return v; }
__device__ __forceinline__ void sts32(uint32_t a, uint32_t v) { asm volatile("st.shared.u32 [%0], %1;" ::"r"(a), "r"(v) : "memory"); }
__device__ __forceinline__ void sts64(uint32_t a, uint32_t x, uint32_t y) { asm volatile("st.shared.v2.u32 [%0], {%1,%2};" ::"r"(a), "r"(x), "r"(y) : "memory"); }
__device__ __forceinline__ void stsf(uint32_t a, float v) { asm volatile("st.shared.f32 [%0], %1;" ::"r"(a), "f"(v) : "memory"); }
__device__ __forceinline__ void sts2f(uint32_t a, float x, float y) { asm volatile("st.shared.v2.f32 [%0], {%1,%2};" ::"r"(a), "f"(x), "f"(y) : "memory"); }
__device__ __forceinline__ void sts4f(uint32_t a, float x, float y, float z, float w) { asm volatile("st.shared.v4.f32 [%0], {%1,%2,%3,%4};" ::"r"(a), "f"(x), "f"(y), "f"(z), "f"(w) : "memory"); }
__device__ __forceinline__ void sts128(uint32_t a, uint32_t x, uint32_t y, uint32_t z, uint32_t w) { asm volatile("st.shared.v4.u32 [%0], {%1,%2,%3,%4};" ::"r"(a), "r"(x), "r"(y), "r"(z), "r"(w) : "memory"); }
__device__ __forceinline__ void ldsm4(uint32_t a, uint32_t& r0, uint32_t& r1, uint32_t& r2, uint32_t& r3) { asm volatile("ldmatrix.sync.aligned.m8n8.x4.shared.b16 {%0,%1,%2,%3}, [%4];" : "=r"(r0), "=r"(r1), "=r"(r2), "=r"(r3) : "r"(a) : "memory"); }
__device__ __forceinline__ void ldsm2(uint32_t a, uint32_t& r0, uint32_t& r1) { asm volatile("ldmatrix.sync.aligned.m8n8.x2.shared.b16 {%0,%1}, [%2];" : "=r"(r0), "=r"(r1) : "r"(a) : "memory"); }
__device__ __forceinline__ void ldsm4t(uint32_t a, uint32_t& r0, uint32_t& r1, uint32_t& r2, uint32_t& r3) { asm volatile("ldmatrix.sync.aligned.m8n8.x4.trans.shared.b16 {%0,%1,%2,%3}, [%4];" : "=r"(r0), "=r"(r1), "=r"(r2), "=r"(r3) : "r"(a) : "memory"); }
__device__ __forceinline__ void stsm4(uint32_t a, uint32_t r0, uint32_t r1, uint32_t r2, uint32_t r3) { asm volatile("stmatrix.sync.aligned.m8n8.x4.shared.b16 [%0], {%1,%2,%3,%4};" ::"r"(a), "r"(r0), "r"(r1), "r"(r2), "r"(r3) : "memory"); }
__device__ __forceinline__ void stsm2(uint32_t a, uint32_t r0, uint32_t r1) { asm volatile("stmatrix.sync.aligned.m8n8.x2.shared.b16 [%0], {%1,%2};" ::"r"(a), "r"(r0), "r"(r1) : "memory"); }
__device__ __forceinline__ void stsm4t(uint32_t a, uint32_t r0, uint32_t r1, uint32_t r2, uint32_t r3) { asm volatile("stmatrix.sync.aligned.m8n8.x4.trans.shared.b16 [%0], {%1,%2,%3,%4};" ::"r"(a), "r"(r0), "r"(r1), "r"(r2), "r"(r3) : "memory"); }
__device__ __forceinline__ void mma16816_bf(float* d, uint32_t a0, uint32_t a1, uint32_t a2, uint32_t a3, uint32_t b0, uint32_t b1) {
  asm volatile("mma.sync.aligned.m16n8k16.row.col.f32.bf16.bf16.f32 {%0,%1,%2,%3}, {%4,%5,%6,%7}, {%8,%9}, {%0,%1,%2,%3};"
               : "+f"(d[0]), "+f"(d[1]), "+f"(d[2]), "+f"(d[3]) : "r"(a0), "r"(a1), "r"(a2), "r"(a3), "r"(b0), "r"(b1));
}
__device__ __forceinline__ void mma16816(float* d, uint32_t a0, uint32_t a1, uint32_t a2, uint32_t a3, uint32_t b0, uint32_t b1) {
  asm volatile("mma.sync.aligned.m16n8k16.row.col.f32.f16.f16.f32 {%0,%1,%2,%3}, {%4,%5,%6,%7}, {%8,%9}, {%0,%1,%2,%3};"
               : "+f"(d[0]), "+f"(d[1]), "+f"(d[2]), "+f"(d[3]) : "r"(a0), "r"(a1), "r"(a2), "r"(a3), "r"(b0), "r"(b1));
}

__device__ __forceinline__ uint32_t pack_bf16(float lo, float hi) { uint32_t r; asm("cvt.rn.bf16x2.f32 %0, %1, %2;" : "=r"(r) : "f"(hi), "f"(lo)); return r; }
__device__ __forceinline__ float bf_lo(uint32_t v) { return __uint_as_float(v << 16); }
__device__ __forceinline__ float bf_hi(uint32_t v) { return __uint_as_float(v & 0xffff0000u); }
__device__ __forceinline__ float round_bf16(float x) { return bf_lo(pack_bf16(x, 0.f)); }
__device__ __forceinline__ uint32_t bf2_mul(uint32_t a, uint32_t b) { uint32_t r; asm("mul.rn.bf16x2 %0, %1, %2;" : "=r"(r) : "r"(a), "r"(b)); return r; }
__device__ __forceinline__ uint32_t bf2_add(uint32_t a, uint32_t b) { uint32_t r; asm("add.rn.bf16x2 %0, %1, %2;" : "=r"(r) : "r"(a), "r"(b)); return r; }
__device__ __forceinline__ uint32_t bf2_sub(uint32_t a, uint32_t b) { uint32_t r; asm("sub.rn.bf16x2 %0, %1, %2;" : "=r"(r) : "r"(a), "r"(b)); return r; }
__device__ __forceinline__ uint32_t dup_bf16(float v) { return pack_bf16(v, v); }
__device__ __forceinline__ float gelu_half(float hx) {
  float u = hx * fmaf(0.2854192648f, hx * hx, 1.5957691216f);
  float t; asm("tanh.approx.f32 %0, %1;" : "=f"(t) : "f"(u));
  return fmaf(hx, t, hx);
}
__device__ __forceinline__ void wait_ready(uint32_t& ready, int need, const uint32_t* flags, int stride, int n, uint32_t target, int lane) {
  if ((ready >> need) & 1) return;
  unsigned it = 0;
#pragma unroll 1
  do {
    uint32_t v = target - 1;
    if (lane < n) asm volatile("ld.relaxed.gpu.global.u32 %0, [%1];" : "=r"(v) : "l"(flags + lane * stride) : "memory");
    ready = __ballot_sync(0xffffffffu, (int)(v - target) >= 0);
  } while (!((ready >> need) & 1) && ++it < SPIN_LIMIT);
  ready |= 1u << need;
  asm volatile("fence.acquire.gpu;" ::: "memory");
  asm volatile("fence.proxy.async.global;" ::: "memory");
  __syncwarp();
}

constexpr uint32_t HI_SW128 = 64u | (1u << 30);
constexpr uint32_t HI_NOSW = 8u;
__device__ __forceinline__ uint32_t desc_lo(uint32_t addr, uint32_t lbo) { return ((addr & 0x3FFFF) >> 4) | ((lbo >> 4) << 16); }

template <uint32_t HA, uint32_t HB>
__device__ __forceinline__ void wgmma_n112_tA(float* d, uint32_t da, uint32_t db, int sd) {
  asm volatile("{.reg .pred p; .reg .b64 a, b; setp.ne.b32 p, %58, 0; mov.b64 a, {%56, %59}; mov.b64 b, {%57, %60};\n"
    "wgmma.mma_async.sync.aligned.m64n112k16.f32.bf16.bf16 {%0,%1,%2,%3,%4,%5,%6,%7,%8,%9,%10,%11,%12,%13,%14,%15,%16,%17,%18,%19,%20,%21,%22,%23,%24,%25,%26,%27,%28,%29,%30,%31,%32,%33,%34,%35,%36,%37,%38,%39,%40,%41,%42,%43,%44,%45,%46,%47,%48,%49,%50,%51,%52,%53,%54,%55}, a, b, p, 1, 1, 1, 0;}"
    : "+f"(d[0]),"+f"(d[1]),"+f"(d[2]),"+f"(d[3]),"+f"(d[4]),"+f"(d[5]),"+f"(d[6]),"+f"(d[7]),"+f"(d[8]),"+f"(d[9]),"+f"(d[10]),"+f"(d[11]),"+f"(d[12]),"+f"(d[13]),"+f"(d[14]),"+f"(d[15]),"+f"(d[16]),"+f"(d[17]),"+f"(d[18]),"+f"(d[19]),"+f"(d[20]),"+f"(d[21]),"+f"(d[22]),"+f"(d[23]),"+f"(d[24]),"+f"(d[25]),"+f"(d[26]),"+f"(d[27]),"+f"(d[28]),"+f"(d[29]),"+f"(d[30]),"+f"(d[31]),"+f"(d[32]),"+f"(d[33]),"+f"(d[34]),"+f"(d[35]),"+f"(d[36]),"+f"(d[37]),"+f"(d[38]),"+f"(d[39]),"+f"(d[40]),"+f"(d[41]),"+f"(d[42]),"+f"(d[43]),"+f"(d[44]),"+f"(d[45]),"+f"(d[46]),"+f"(d[47]),"+f"(d[48]),"+f"(d[49]),"+f"(d[50]),"+f"(d[51]),"+f"(d[52]),"+f"(d[53]),"+f"(d[54]),"+f"(d[55])
    : "r"(da), "r"(db), "r"(sd), "n"(HA), "n"(HB));
}
template <uint32_t HA, uint32_t HB>
__device__ __forceinline__ void wgmma_n112(float* d, uint32_t da, uint32_t db, int sd) {
  asm volatile("{.reg .pred p; .reg .b64 a, b; setp.ne.b32 p, %58, 0; mov.b64 a, {%56, %59}; mov.b64 b, {%57, %60};\n"
    "wgmma.mma_async.sync.aligned.m64n112k16.f32.bf16.bf16 {%0,%1,%2,%3,%4,%5,%6,%7,%8,%9,%10,%11,%12,%13,%14,%15,%16,%17,%18,%19,%20,%21,%22,%23,%24,%25,%26,%27,%28,%29,%30,%31,%32,%33,%34,%35,%36,%37,%38,%39,%40,%41,%42,%43,%44,%45,%46,%47,%48,%49,%50,%51,%52,%53,%54,%55}, a, b, p, 1, 1, 0, 0;}"
    : "+f"(d[0]),"+f"(d[1]),"+f"(d[2]),"+f"(d[3]),"+f"(d[4]),"+f"(d[5]),"+f"(d[6]),"+f"(d[7]),"+f"(d[8]),"+f"(d[9]),"+f"(d[10]),"+f"(d[11]),"+f"(d[12]),"+f"(d[13]),"+f"(d[14]),"+f"(d[15]),"+f"(d[16]),"+f"(d[17]),"+f"(d[18]),"+f"(d[19]),"+f"(d[20]),"+f"(d[21]),"+f"(d[22]),"+f"(d[23]),"+f"(d[24]),"+f"(d[25]),"+f"(d[26]),"+f"(d[27]),"+f"(d[28]),"+f"(d[29]),"+f"(d[30]),"+f"(d[31]),"+f"(d[32]),"+f"(d[33]),"+f"(d[34]),"+f"(d[35]),"+f"(d[36]),"+f"(d[37]),"+f"(d[38]),"+f"(d[39]),"+f"(d[40]),"+f"(d[41]),"+f"(d[42]),"+f"(d[43]),"+f"(d[44]),"+f"(d[45]),"+f"(d[46]),"+f"(d[47]),"+f"(d[48]),"+f"(d[49]),"+f"(d[50]),"+f"(d[51]),"+f"(d[52]),"+f"(d[53]),"+f"(d[54]),"+f"(d[55])
    : "r"(da), "r"(db), "r"(sd), "n"(HA), "n"(HB));
}
template <uint32_t HA, uint32_t HB>
__device__ __forceinline__ void wgmma_n56_tB(float* d, uint32_t da, uint32_t db, int sd) {
  asm volatile("{.reg .pred p; .reg .b64 a, b; setp.ne.b32 p, %30, 0; mov.b64 a, {%28, %31}; mov.b64 b, {%29, %32};\n"
    "wgmma.mma_async.sync.aligned.m64n56k16.f32.bf16.bf16 {%0,%1,%2,%3,%4,%5,%6,%7,%8,%9,%10,%11,%12,%13,%14,%15,%16,%17,%18,%19,%20,%21,%22,%23,%24,%25,%26,%27}, a, b, p, 1, 1, 0, 1;}"
    : "+f"(d[0]),"+f"(d[1]),"+f"(d[2]),"+f"(d[3]),"+f"(d[4]),"+f"(d[5]),"+f"(d[6]),"+f"(d[7]),"+f"(d[8]),"+f"(d[9]),"+f"(d[10]),"+f"(d[11]),"+f"(d[12]),"+f"(d[13]),"+f"(d[14]),"+f"(d[15]),"+f"(d[16]),"+f"(d[17]),"+f"(d[18]),"+f"(d[19]),"+f"(d[20]),"+f"(d[21]),"+f"(d[22]),"+f"(d[23]),"+f"(d[24]),"+f"(d[25]),"+f"(d[26]),"+f"(d[27])
    : "r"(da), "r"(db), "r"(sd), "n"(HA), "n"(HB));
}
template <uint32_t HB>
__device__ __forceinline__ void wgmma_rs112(float* d, uint32_t a0, uint32_t a1, uint32_t a2, uint32_t a3, uint32_t db, int sd) {
  asm volatile("{.reg .pred p; .reg .b64 b; setp.ne.b32 p, %61, 0; mov.b64 b, {%60, %62};\n"
    "wgmma.mma_async.sync.aligned.m64n112k16.f32.bf16.bf16 {%0,%1,%2,%3,%4,%5,%6,%7,%8,%9,%10,%11,%12,%13,%14,%15,%16,%17,%18,%19,%20,%21,%22,%23,%24,%25,%26,%27,%28,%29,%30,%31,%32,%33,%34,%35,%36,%37,%38,%39,%40,%41,%42,%43,%44,%45,%46,%47,%48,%49,%50,%51,%52,%53,%54,%55}, {%56,%57,%58,%59}, b, p, 1, 1, 0;}"
    : "+f"(d[0]),"+f"(d[1]),"+f"(d[2]),"+f"(d[3]),"+f"(d[4]),"+f"(d[5]),"+f"(d[6]),"+f"(d[7]),"+f"(d[8]),"+f"(d[9]),"+f"(d[10]),"+f"(d[11]),"+f"(d[12]),"+f"(d[13]),"+f"(d[14]),"+f"(d[15]),"+f"(d[16]),"+f"(d[17]),"+f"(d[18]),"+f"(d[19]),"+f"(d[20]),"+f"(d[21]),"+f"(d[22]),"+f"(d[23]),"+f"(d[24]),"+f"(d[25]),"+f"(d[26]),"+f"(d[27]),"+f"(d[28]),"+f"(d[29]),"+f"(d[30]),"+f"(d[31]),"+f"(d[32]),"+f"(d[33]),"+f"(d[34]),"+f"(d[35]),"+f"(d[36]),"+f"(d[37]),"+f"(d[38]),"+f"(d[39]),"+f"(d[40]),"+f"(d[41]),"+f"(d[42]),"+f"(d[43]),"+f"(d[44]),"+f"(d[45]),"+f"(d[46]),"+f"(d[47]),"+f"(d[48]),"+f"(d[49]),"+f"(d[50]),"+f"(d[51]),"+f"(d[52]),"+f"(d[53]),"+f"(d[54]),"+f"(d[55])
    : "r"(a0), "r"(a1), "r"(a2), "r"(a3), "r"(db), "r"(sd), "n"(HB));
}
template <uint32_t HB>
__device__ __forceinline__ void wgmma_rs128(float* d, uint32_t a0, uint32_t a1, uint32_t a2, uint32_t a3, uint32_t db, int sd) {
  asm volatile("{.reg .pred p; .reg .b64 b; setp.ne.b32 p, %69, 0; mov.b64 b, {%68, %70};\n"
    "wgmma.mma_async.sync.aligned.m64n128k16.f32.bf16.bf16 {%0,%1,%2,%3,%4,%5,%6,%7,%8,%9,%10,%11,%12,%13,%14,%15,%16,%17,%18,%19,%20,%21,%22,%23,%24,%25,%26,%27,%28,%29,%30,%31,%32,%33,%34,%35,%36,%37,%38,%39,%40,%41,%42,%43,%44,%45,%46,%47,%48,%49,%50,%51,%52,%53,%54,%55,%56,%57,%58,%59,%60,%61,%62,%63}, {%64,%65,%66,%67}, b, p, 1, 1, 0;}"
    : "+f"(d[0]),"+f"(d[1]),"+f"(d[2]),"+f"(d[3]),"+f"(d[4]),"+f"(d[5]),"+f"(d[6]),"+f"(d[7]),"+f"(d[8]),"+f"(d[9]),"+f"(d[10]),"+f"(d[11]),"+f"(d[12]),"+f"(d[13]),"+f"(d[14]),"+f"(d[15]),"+f"(d[16]),"+f"(d[17]),"+f"(d[18]),"+f"(d[19]),"+f"(d[20]),"+f"(d[21]),"+f"(d[22]),"+f"(d[23]),"+f"(d[24]),"+f"(d[25]),"+f"(d[26]),"+f"(d[27]),"+f"(d[28]),"+f"(d[29]),"+f"(d[30]),"+f"(d[31]),"+f"(d[32]),"+f"(d[33]),"+f"(d[34]),"+f"(d[35]),"+f"(d[36]),"+f"(d[37]),"+f"(d[38]),"+f"(d[39]),"+f"(d[40]),"+f"(d[41]),"+f"(d[42]),"+f"(d[43]),"+f"(d[44]),"+f"(d[45]),"+f"(d[46]),"+f"(d[47]),"+f"(d[48]),"+f"(d[49]),"+f"(d[50]),"+f"(d[51]),"+f"(d[52]),"+f"(d[53]),"+f"(d[54]),"+f"(d[55]),"+f"(d[56]),"+f"(d[57]),"+f"(d[58]),"+f"(d[59]),"+f"(d[60]),"+f"(d[61]),"+f"(d[62]),"+f"(d[63])
    : "r"(a0), "r"(a1), "r"(a2), "r"(a3), "r"(db), "r"(sd), "n"(HB));
}
template <uint32_t HB>
__device__ __forceinline__ void wgmma_rs96(float* d, uint32_t a0, uint32_t a1, uint32_t a2, uint32_t a3, uint32_t db, int sd) {
  asm volatile("{.reg .pred p; .reg .b64 b; setp.ne.b32 p, %53, 0; mov.b64 b, {%52, %54};\n"
    "wgmma.mma_async.sync.aligned.m64n96k16.f32.bf16.bf16 {%0,%1,%2,%3,%4,%5,%6,%7,%8,%9,%10,%11,%12,%13,%14,%15,%16,%17,%18,%19,%20,%21,%22,%23,%24,%25,%26,%27,%28,%29,%30,%31,%32,%33,%34,%35,%36,%37,%38,%39,%40,%41,%42,%43,%44,%45,%46,%47}, {%48,%49,%50,%51}, b, p, 1, 1, 0;}"
    : "+f"(d[0]),"+f"(d[1]),"+f"(d[2]),"+f"(d[3]),"+f"(d[4]),"+f"(d[5]),"+f"(d[6]),"+f"(d[7]),"+f"(d[8]),"+f"(d[9]),"+f"(d[10]),"+f"(d[11]),"+f"(d[12]),"+f"(d[13]),"+f"(d[14]),"+f"(d[15]),"+f"(d[16]),"+f"(d[17]),"+f"(d[18]),"+f"(d[19]),"+f"(d[20]),"+f"(d[21]),"+f"(d[22]),"+f"(d[23]),"+f"(d[24]),"+f"(d[25]),"+f"(d[26]),"+f"(d[27]),"+f"(d[28]),"+f"(d[29]),"+f"(d[30]),"+f"(d[31]),"+f"(d[32]),"+f"(d[33]),"+f"(d[34]),"+f"(d[35]),"+f"(d[36]),"+f"(d[37]),"+f"(d[38]),"+f"(d[39]),"+f"(d[40]),"+f"(d[41]),"+f"(d[42]),"+f"(d[43]),"+f"(d[44]),"+f"(d[45]),"+f"(d[46]),"+f"(d[47])
    : "r"(a0), "r"(a1), "r"(a2), "r"(a3), "r"(db), "r"(sd), "n"(HB));
}
template <uint32_t HB>
__device__ __forceinline__ void wgmma_rs64(float* d, uint32_t a0, uint32_t a1, uint32_t a2, uint32_t a3, uint32_t db, int sd) {
  asm volatile("{.reg .pred p; .reg .b64 b; setp.ne.b32 p, %37, 0; mov.b64 b, {%36, %38};\n"
    "wgmma.mma_async.sync.aligned.m64n64k16.f32.bf16.bf16 {%0,%1,%2,%3,%4,%5,%6,%7,%8,%9,%10,%11,%12,%13,%14,%15,%16,%17,%18,%19,%20,%21,%22,%23,%24,%25,%26,%27,%28,%29,%30,%31}, {%32,%33,%34,%35}, b, p, 1, 1, 0;}"
    : "+f"(d[0]),"+f"(d[1]),"+f"(d[2]),"+f"(d[3]),"+f"(d[4]),"+f"(d[5]),"+f"(d[6]),"+f"(d[7]),"+f"(d[8]),"+f"(d[9]),"+f"(d[10]),"+f"(d[11]),"+f"(d[12]),"+f"(d[13]),"+f"(d[14]),"+f"(d[15]),"+f"(d[16]),"+f"(d[17]),"+f"(d[18]),"+f"(d[19]),"+f"(d[20]),"+f"(d[21]),"+f"(d[22]),"+f"(d[23]),"+f"(d[24]),"+f"(d[25]),"+f"(d[26]),"+f"(d[27]),"+f"(d[28]),"+f"(d[29]),"+f"(d[30]),"+f"(d[31])
    : "r"(a0), "r"(a1), "r"(a2), "r"(a3), "r"(db), "r"(sd), "n"(HB));
}
template <uint32_t HB>
__device__ __forceinline__ void wgmma_rs32(float* d, uint32_t a0, uint32_t a1, uint32_t a2, uint32_t a3, uint32_t db, int sd) {
  asm volatile("{.reg .pred p; .reg .b64 b; setp.ne.b32 p, %21, 0; mov.b64 b, {%20, %22};\n"
    "wgmma.mma_async.sync.aligned.m64n32k16.f32.bf16.bf16 {%0,%1,%2,%3,%4,%5,%6,%7,%8,%9,%10,%11,%12,%13,%14,%15}, {%16,%17,%18,%19}, b, p, 1, 1, 0;}"
    : "+f"(d[0]),"+f"(d[1]),"+f"(d[2]),"+f"(d[3]),"+f"(d[4]),"+f"(d[5]),"+f"(d[6]),"+f"(d[7]),"+f"(d[8]),"+f"(d[9]),"+f"(d[10]),"+f"(d[11]),"+f"(d[12]),"+f"(d[13]),"+f"(d[14]),"+f"(d[15])
    : "r"(a0), "r"(a1), "r"(a2), "r"(a3), "r"(db), "r"(sd), "n"(HB));
}


__device__ __forceinline__ int k_order(int u, int ti) { return ((u - 2) >> 1) == ti ? 30 + (u & 1) : u - 2; }

enum { BAR_WG0 = 1, BAR_WG1 = 2, BAR_WG2 = 3, BAR_CONS = 4, BAR_K3 = 6, BAR_AUX = 9, BAR_PP0 = 10, BAR_PP1 = 11, BAR_SC = 12, BAR_TAB = 13, BAR_MMA = 14 };

struct Cplx { float r, i; };
__device__ __forceinline__ Cplx cmul(Cplx a, Cplx b) { Cplx o; o.r = fmaf(a.r, b.r, -a.i * b.i); o.i = fmaf(a.r, b.i, a.i * b.r); return o; }
__device__ __forceinline__ Cplx cexp_scaled(float ar2, float air, float s) {
  float m; asm("ex2.approx.ftz.f32 %0, %1;" : "=f"(m) : "f"(ar2 * s));
  float rev = air * s; rev -= rintf(rev);
  float ang = rev * 6.283185307179586f;
  Cplx o; o.r = m * __cosf(ang); o.i = m * __sinf(ang); return o;
}

struct GenParams { uint32_t are, aim, bre, bim, cre, cim, ldt; };
__device__ __forceinline__ GenParams load_gen_params(const Params& p, int d, int tw) {
  GenParams g; size_t o = (size_t)d * NMODE + 2 * tw;
  g.are = __ldg((const uint32_t*)(p.a_re + o)); g.aim = __ldg((const uint32_t*)(p.a_im + o));
  g.bre = __ldg((const uint32_t*)(p.b_re + o)); g.bim = __ldg((const uint32_t*)(p.b_im + o));
  g.cre = __ldg((const uint32_t*)(p.c_re + o)); g.cim = __ldg((const uint32_t*)(p.c_im + o));
  g.ldt = __ldg(reinterpret_cast<const unsigned short*>(p.log_dt + d) + (tw & p.zero));
  return g;
}
struct H2c { __half2 r, i; };
__device__ __forceinline__ H2c hpack(Cplx a, Cplx b) { H2c o; o.r = __floats2half2_rn(a.r, b.r); o.i = __floats2half2_rn(a.i, b.i); return o; }
__device__ __forceinline__ H2c hmul(H2c a, H2c b) {
  H2c o; o.r = __hfma2(a.r, b.r, __hneg2(__hmul2(a.i, b.i))); o.i = __hfma2(a.r, b.i, __hmul2(a.i, b.r)); return o;
}
__device__ __forceinline__ uint32_t h2u(__half2 v) { return *reinterpret_cast<uint32_t*>(&v); }
__device__ __forceinline__ __half2 u2h(uint32_t v) { return *reinterpret_cast<__half2*>(&v); }
__device__ __forceinline__ void hstore(uint32_t a, H2c v) { sts32(a, h2u(v.r)); sts32(a + 128, h2u(v.i)); }
__device__ __forceinline__ void qstore(uint32_t a, H2c v) { sts64(a, h2u(v.r), h2u(v.i)); }
__device__ __forceinline__ H2c qload(uint32_t a) { const float2 t = lds2f(a); H2c o; o.r = *reinterpret_cast<const __half2*>(&t.x); o.i = *reinterpret_cast<const __half2*>(&t.y); return o; }
__device__ __forceinline__ Cplx csq(Cplx a) { Cplx o; o.r = fmaf(a.r, a.r, -a.i * a.i); o.i = (a.r + a.r) * a.i; return o; }

__device__ __forceinline__ void gen_kernel(const Params& p, GenParams& gp, uint32_t wgbuf, uint32_t ktab, int tw, int barid, uint32_t* pub, int next, const uint4* nxp, uint32_t nxt, uint4 (&nx)[2][4]) {
  asm volatile("" : "+r"(tw));
  const int lane = tw & 31, wp = tw >> 5, g = lane >> 2, c = lane & 3;
  const uint32_t buf = wgbuf + wp * GEN_BYTES;
  const uint32_t col = buf + lane * 4;
  const float dt = round_bf16(__expf(__uint_as_float(gp.ldt << 16)));
  Cplx cf[2], z[2], y[2], w[2];
#pragma unroll
  for (int m = 0; m < 2; m++) {
    const float are = m ? bf_hi(gp.are) : bf_lo(gp.are), aim = m ? bf_hi(gp.aim) : bf_lo(gp.aim);
    const float bre = dt * (m ? bf_hi(gp.bre) : bf_lo(gp.bre)), bim = dt * (m ? bf_hi(gp.bim) : bf_lo(gp.bim));
    const float cre = m ? bf_hi(gp.cre) : bf_lo(gp.cre), cim = m ? bf_hi(gp.cim) : bf_lo(gp.cim);
    const float ar2 = (dt * are) * 1.4426950408889634f, air = (dt * aim) * 0.15915494309189535f;
    cf[m].r = cre * bre - cim * bim; cf[m].i = cre * bim + cim * bre;
    z[m] = cexp_scaled(ar2, air, 1.f); y[m] = cexp_scaled(ar2, air, 256.f);
  }
  if (next >= 0) gp = load_gen_params(p, next, tw + (__float_as_uint(cf[0].r + z[1].i + y[1].r) & p.zero));
  if (pub && (__float_as_uint(y[0].r + y[1].i) & p.zero) == 0) {
    asm volatile("cp.async.bulk.wait_group 0;" ::: "memory");
    red_rlx(pub, 1u);
  }
  __syncwarp();
  const uint32_t mx = __reduce_max_sync(0xffffffffu, __float_as_uint(fmaxf(fmaxf(fabsf(cf[0].r), fabsf(cf[0].i)), fmaxf(fabsf(cf[1].r), fabsf(cf[1].i)))));
  const uint32_t ex = min(max(mx >> 23, 1u), 253u);
  const float scale = __uint_as_float((254u - ex) << 23), unscale = __uint_as_float(ex << 23);
  {
    Cplx z2[2], z3[2], z4[2], t[2];
#pragma unroll
    for (int m = 0; m < 2; m++) {
      z2[m] = csq(z[m]); z3[m] = cmul(z2[m], z[m]); z4[m] = csq(z2[m]); t[m].r = cf[m].r * scale; t[m].i = cf[m].i * scale;
      w[m] = csq(z4[m]); w[m].i = -w[m].i;
    }
    const H2c h1 = hpack(z[0], z[1]), h2 = hpack(z2[0], z2[1]), h3 = hpack(z3[0], z3[1]), h4 = hpack(z4[0], z4[1]);
    H2c x = hpack(t[0], t[1]);
    hstore(col, x); hstore(col + GEN_PITCH, hmul(x, h1)); hstore(col + 2 * GEN_PITCH, hmul(x, h2)); hstore(col + 3 * GEN_PITCH, hmul(x, h3));
    x = hmul(x, h4);
    hstore(col + 4 * GEN_PITCH, x); hstore(col + 5 * GEN_PITCH, hmul(x, h1)); hstore(col + 6 * GEN_PITCH, hmul(x, h2)); hstore(col + 7 * GEN_PITCH, hmul(x, h3));
    t[0] = cmul(t[0], y[0]); t[1] = cmul(t[1], y[1]); x = hpack(t[0], t[1]);
    hstore(col + 8 * GEN_PITCH, x); hstore(col + 9 * GEN_PITCH, hmul(x, h2));
    x = hmul(x, h4);
    hstore(col + 10 * GEN_PITCH, x); hstore(col + 11 * GEN_PITCH, hmul(x, h2));
#pragma unroll
    for (int k = 0; k < 2; k++) {
      t[0] = cmul(t[0], y[0]); t[1] = cmul(t[1], y[1]); x = hpack(t[0], t[1]);
      hstore(col + (12 + 2 * k) * GEN_PITCH, x); hstore(col + (13 + 2 * k) * GEN_PITCH, hmul(x, h4));
    }
#pragma unroll
    for (int k = 0; k < 5; k++) { t[0] = cmul(t[0], y[0]); t[1] = cmul(t[1], y[1]); hstore(col + (16 + k) * GEN_PITCH, hpack(t[0], t[1])); }
  }
  {
    Cplx w2[2], w4[2], w8[2], w16[2];
#pragma unroll
    for (int m = 0; m < 2; m++) { w2[m] = csq(w[m]); w4[m] = csq(w2[m]); w8[m] = csq(w4[m]); w16[m] = csq(w8[m]); }
    H2c q[8];
    q[1] = hpack(w[0], w[1]); q[2] = hpack(w2[0], w2[1]); q[4] = hpack(w4[0], w4[1]); q[3] = hmul(q[1], q[2]);
    q[5] = hmul(q[4], q[1]); q[6] = hmul(q[4], q[2]); q[7] = hmul(q[4], q[3]);
    const H2c q8 = hpack(w8[0], w8[1]);
    const uint32_t qo = buf + GEN_Q + lane * 16, qo1 = buf + GEN_Q + (lane ^ 4) * 16;
    sts128(qo, 0x3c003c00u, h2u(q8.r), 0u, h2u(q8.i));
#pragma unroll
    for (int e = 1; e < 8; e++) { const H2c r = hmul(q[e], q8); sts128((e & 1 ? qo1 : qo) + e * GEN_QP, h2u(q[e].r), h2u(r.r), h2u(q[e].i), h2u(r.i)); }
    qstore(buf + GEN_Q + 8 * GEN_QP + lane * 8, hpack(w16[0], w16[1]));
  }
  __syncwarp();
  float acc[2][3][4];
#pragma unroll
  for (int u = 0; u < 6; u++)
#pragma unroll
    for (int e = 0; e < 4; e++) acc[u / 3][u % 3][e] = 0.f;
  {
    const uint32_t baddr = buf + ((lane & 7) + (lane >> 4) * 8) * GEN_PITCH + ((lane >> 3) & 1) * 128;
    const uint32_t baddr2 = buf + (16 + (lane & 7)) * GEN_PITCH + ((lane >> 3) & 1) * 128;
    const uint32_t qaddr = buf + GEN_Q + g * GEN_QP + c * 16, paddr = buf + GEN_Q + 8 * GEN_QP + c * 8;
#pragma unroll 1
    for (int k0 = 0; k0 < 8; k0 += 4) {
      uint32_t bf[4][6];
      uint4 e0[4];
      H2c p16[4];
#pragma unroll
      for (int u = 0; u < 4; u++) {
        e0[u] = lds128(qaddr + k0 * 64 + (u & 2) * 64 + ((u ^ g) & 1) * 64); p16[u] = qload(paddr + (k0 + u) * 32);
        ldsm4(baddr + (k0 + u) * 16, bf[u][0], bf[u][1], bf[u][2], bf[u][3]); ldsm2(baddr2 + (k0 + u) * 16, bf[u][4], bf[u][5]);
      }
#pragma unroll
      for (int u = 0; u < 4; u++) {
        H2c ea, eb;
        ea.r = u2h(e0[u].x); ea.i = u2h(e0[u].z); eb.r = u2h(e0[u].y); eb.i = u2h(e0[u].w);
        const H2c e2 = hmul(ea, p16[u]), e3 = hmul(eb, p16[u]);
#pragma unroll
        for (int nt = 0; nt < 3; nt++) {
          mma16816(acc[0][nt], e0[u].x, e0[u].y, e0[u].z, e0[u].w, bf[u][2 * nt], bf[u][2 * nt + 1]);
          mma16816(acc[1][nt], h2u(e2.r), h2u(e3.r), h2u(e2.i), h2u(e3.i), bf[u][2 * nt], bf[u][2 * nt + 1]);
        }
      }
    }
  }
  if (!nxp && next < 0) bar_arrive(BAR_MMA, 384);
  const uint32_t gv = ld_rlx(p.s->cnt_nx);
  __syncwarp();
#pragma unroll
  for (int u = 0; u < 6; u++) sts4f(buf + (u * 32 + lane) * 16, acc[u / 3][u % 3][0] * unscale, acc[u / 3][u % 3][1] * unscale, acc[u / 3][u % 3][2] * unscale, acc[u / 3][u % 3][3] * unscale);
  bar_sync(barid, 128);
  if (nxp) {
    if ((int)(gv - nxt) < 0) gate_wait(p.s->cnt_nx, nxt);
#pragma unroll
    for (int u = 0; u < 8; u++) nx[u >> 2][u & 3] = ld_rlx4(nxp + (u >> 2) * (SEQ / 2) + (u & 3) * 128);
  }
  const uint32_t kd = wgbuf + 4096;
  {
    float2 pp[3][4];
#pragma unroll
    for (int nt = 0; nt < 3; nt++)
#pragma unroll
      for (int u = 0; u < 4; u++) pp[nt][u] = lds2f(wgbuf + (((wp >> 1) * 3 + nt) * 32 + lane) * 16 + (wp & 1) * 8 + u * GEN_BYTES);
    const int j = 8 * wp + g;
#pragma unroll
    for (int nt = 0; nt < 3; nt++) {
      int i0, i1;
      if (nt == 0) { i0 = 8 * j + 2 * c; i1 = i0 + 1; }
      else if (nt == 1) { i0 = c < 2 ? 256 + 4 * j + 2 * c : 384 + 64 * (c - 2) + 2 * j; i1 = i0 + 1; }
      else { i0 = 512 + 64 * c + j; i1 = i0 + 32; }
      const float v0 = (pp[nt][0].x + pp[nt][1].x) + (pp[nt][2].x + pp[nt][3].x), v1 = (pp[nt][0].y + pp[nt][1].y) + (pp[nt][2].y + pp[nt][3].y);
      if (nt < 2) sts2f(kd + i0 * 4, v0, v1);
      else { if (i0 <= 640) stsf(kd + i0 * 4, v0); if (c < 2) stsf(kd + i1 * 4, v1); }
    }
  }
  bar_sync(barid, 128);
  {
    const uint32_t o = ktab + (8 + tw) * 4;
    const uint32_t kb0 = kd - (0x4300 - 128) * 4;
    float ka[8], kb[8], kc[8];
    ka[0] = ldsf(kd + max(2 * tw - 1, 0) * 4);
    { const float2 t = lds2f(kd + tw * 8); kb[0] = t.x; kc[0] = t.y; }
#pragma unroll
    for (int s = 1; s < 8; s *= 2) {
      const int l = 2 * (tw + 128 * s);
      const uint32_t i0 = pack_bf16((float)(l - 1), (float)l), i1 = pack_bf16((float)(l + 1), 0.f);
      const uint32_t pa = kb0 + (i0 & 0xffffu) * 4, pb = kb0 + (i0 >> 16) * 4, pc = kb0 + i1 * 4;
#pragma unroll
      for (int e = 0; e < s; e++) { ka[s + e] = ldsf(pa + e * (512 / s)); kb[s + e] = ldsf(pb + e * (512 / s)); kc[s + e] = ldsf(pc + e * (512 / s)); }
    }
    if (tw == 0) ka[0] = 0.f;
#pragma unroll
    for (int e = 0; e < 8; e++) { sts32(o + e * 512, pack_bf16(kb[e], ka[e])); sts32(o + KTAB_ODD + e * 512, pack_bf16(kc[e], kb[e])); }
    if (tw < 4) sts128(ktab + (tw & 1) * 16 + (tw >> 1) * KTAB_ODD, 0, 0, 0, 0);
  }
}

__device__ __forceinline__ void ln1_publish(const Params& p, GenParams& gp, const CUtensorMap* tmnx, const uint32_t (&v)[2][7], uint32_t sb, int bid, int tid) {
  const int lane = tid & 31, warp = tid >> 5;
  uint32_t m2[2];
  float rs[2];
  float s[2], q[2], sh[2];
#pragma unroll
  for (int r = 0; r < 2; r++) {
    sh[r] = bf_lo(__shfl_sync(0xffffffffu, v[r][0], 0));
    s[r] = 0.f; q[r] = 0.f;
#pragma unroll
    for (int k = 0; k < 7; k++) {
      const float a = bf_lo(v[r][k]) - sh[r], b = bf_hi(v[r][k]) - sh[r];
      s[r] += a + b; q[r] = fmaf(a, a, fmaf(b, b, q[r]));
    }
  }
  if (bid < NCONV) gp = load_gen_params(p, 4 * bid + 2 - (warp >> 2), (tid & 127) + ((__float_as_uint(q[0]) ^ __float_as_uint(q[1])) & p.zero));
#pragma unroll
  for (int o = 16; o; o >>= 1)
#pragma unroll
    for (int r = 0; r < 2; r++) { s[r] += __shfl_xor_sync(0xffffffffu, s[r], o); q[r] += __shfl_xor_sync(0xffffffffu, q[r], o); }
#pragma unroll
  for (int r = 0; r < 2; r++) {
    const float md = s[r] * (1.f / DM), var = fmaxf(q[r] * (1.f / DM) - md * md, 0.f);
    float sd; asm("sqrt.approx.f32 %0, %1;" : "=f"(sd) : "f"(round_bf16(round_bf16(var) + 1e-5f)));
    asm("rcp.approx.f32 %0, %1;" : "=f"(rs[r]) : "f"(round_bf16(sd)));
    m2[r] = dup_bf16(sh[r] + md);
  }
  const bool flip = (lane >> 2) & 1;
  const uint32_t tb = sb + OFF_TR + lane * 128 + (warp & 1) * 8;
  const uint32_t s0 = (uint32_t)(((warp >> 1) ^ (lane & 3)) * 16) + (flip ? 64u : 0u), s1 = s0 ^ 64u;
  const uint32_t sel0 = flip ? 0x7632u : 0x5410u, sel1 = flip ? 0x5410u : 0x7632u;
#pragma unroll
  for (int k = 0; k < 7; k++) {
    uint32_t w[2][2];
#pragma unroll
    for (int r = 0; r < 2; r++) {
      const uint32_t d = bf2_sub(v[r][k], m2[r]);
      const uint32_t n = pack_bf16(bf_lo(d) * rs[r], bf_hi(d) * rs[r]);
      w[r][0] = __byte_perm(n, v[r][k], sel0); w[r][1] = __byte_perm(n, v[r][k], sel1);
    }
    sts64(tb + k * 4096 + s0, w[0][0], w[1][0]);
    sts64(tb + k * 4096 + s1, w[0][1], w[1][1]);
  }
  fence_async_smem();
  bar_sync(BAR_CONS, 256);
  if (tid == 0) {
    asm volatile("cp.async.bulk.tensor.2d.global.shared::cta.bulk_group [%0, {%1, %2}], [%3];" ::"l"(tmnx), "r"(16 * bid), "r"(0), "r"(sb + OFF_TR) : "memory");
    asm volatile("cp.async.bulk.tensor.2d.global.shared::cta.bulk_group [%0, {%1, %2}], [%3];" ::"l"(tmnx), "r"(16 * bid), "r"(224), "r"(sb + OFF_TR + 14336) : "memory");
    asm volatile("cp.async.bulk.commit_group;" ::: "memory");
  }
}

__device__ __forceinline__ void conv_channels(const Params& p, uint32_t sb, int cidx, int tw, int wg) {
  const int lane = tw & 31, h = tw >> 5;
  const int g = lane >> 2, c = lane & 3;
  uint32_t kt = sb + OFF_KTAB + wg * KTAB_CH + (g & 1) * KTAB_ODD + (8 + 64 * h + (g >> 1) - c - 4) * 4;
  const uint32_t red = sb + OFF_RED + wg * 24576 + lane * 16, rw = red + h * 512;
  uint32_t rr[3];
#pragma unroll
  for (int u = 1; u < 4; u++) rr[u - 1] = red + (h + u < 4 ? (h - 3 * u) * 512 : (8 + h - 3 * u) * 512);
  const int blk = 8 * h + (lane & 7) + (lane >> 4) * 32, mhalf = (lane >> 3) & 1;
  uint32_t ha = sb + OFF_H + wg * H_CH + mhalf * H_HI + (8 + blk) * 16;
  uint32_t xa = sb + OFF_X + (wg - 2) * X_CH + (blk >> 2) * 128 + ((((blk & 3) * 2 + mhalf) ^ (cidx & 7)) * 16);
  float acc[64], ac1[48], ac2[32], ac3[16];
  uint32_t wa[17], wb[17];
  float y[4][4];
  uint32_t hv[2][4], xv[2][4], ga2;
#define CONV_FIN(PP, M) { const float* yy = &y[2 * (PP) + ((M) >> 1)][2 * ((M) & 1)];                                    \
  xv[PP][M] = bf2_add(xv[PP][M], bf2_mul(ga2, bf2_add(pack_bf16(yy[0], yy[1]), hv[PP][M]))); }
#define CONV_TAIL(R)                                                                                                     \
  bar_sync(BAR_WG0 + wg, 128);                                                                                           \
  CONV_GET(y[3], 3)                                                                                                      \
  CONV_FIN(1, 2) CONV_FIN(1, 3)                                                                                          \
  stsm4t(xa + 2048, xv[1][0], xv[1][1], xv[1][2], xv[1][3]);                                                             \
  fence_async_smem();                                                                                                    \
  __syncwarp();                                                                                                          \
  if (lane == 0) mbar_arrive(sb + OFF_PUB + (wg * 4 + (R)) * 8);
#define CONV_LOAD(W, K) _Pragma("unroll") for (int e = 0; e < 17; e++) W[e] = lds32(kt + (K) * 1024 + e * 16);
#define CONV_MMA(FN, ACC, W, K)                                                                                          \
  bar_sync(BAR_PP0 + wg, 256);                                                                                           \
  wg_fence();                                                                                                            \
  _Pragma("unroll") for (int s = 0; s < 8; s++) FN<HI_NOSW>(ACC, W[2 * s + 1], W[2 * s + 2], W[2 * s], W[2 * s + 1], db - s, (K) + s != 0); \
  wg_commit();                                                                                                           \
  bar_arrive(BAR_PP1 - wg, 256);
#define CONV_MOVE(DST, SRC, N) _Pragma("unroll") for (int e = 0; e < N; e++) asm volatile("mov.f32 %0, %1;" : "=f"(DST[e]) : "f"(SRC[16 + e]));
#define CONV_PUT(SRC, M) _Pragma("unroll") for (int e = 1; e < 4; e++) if ((M) < 3 || e + h < 4) sts4f(rw + (3 * (M) + e - 1) * 2048, SRC[4 * e], SRC[4 * e + 1], SRC[4 * e + 2], SRC[4 * e + 3]);
#define CONV_GET(SRC, M) { float4 t[3];                                                                                  \
  _Pragma("unroll") for (int u = 0; u < 3; u++) t[u] = ((M) > 0 || h + u >= 3) ? lds4f(rr[u] + (M) * 6144) : make_float4(0.f, 0.f, 0.f, 0.f); \
  y[M][0] = (SRC[0] + t[0].x) + (t[1].x + t[2].x); y[M][1] = (SRC[1] + t[0].y) + (t[1].y + t[2].y);                      \
  y[M][2] = (SRC[2] + t[0].z) + (t[1].z + t[2].z); y[M][3] = (SRC[3] + t[0].w) + (t[1].w + t[2].w); }
  CONV_LOAD(wa, 0)
  if (wg == 1) bar_arrive(BAR_PP0, 256);
#pragma unroll 1
  for (int round = 0; round < 2; round++) {
    const uint32_t db = desc_lo(sb + OFF_H + (wg + 2 * round) * H_CH + 8 * 16, H_HI);
    CONV_MMA(wgmma_rs128, acc, wa, 0)
    CONV_LOAD(wb, 1)
    if (round > 0) { CONV_TAIL(0) }
    wg_wait<0>();
    CONV_MOVE(ac1, acc, 48)
    CONV_MMA(wgmma_rs96, ac1, wb, 1)
    CONV_LOAD(wa, 2)
    CONV_PUT(acc, 0)
    bar_sync(BAR_WG0 + wg, 128);
    CONV_GET(acc, 0)
    wg_wait<0>();
    CONV_MOVE(ac2, ac1, 32)
    CONV_MMA(wgmma_rs64, ac2, wa, 2)
    CONV_LOAD(wb, 3)
    CONV_PUT(ac1, 1)
    bar_sync(BAR_WG0 + wg, 128);
    CONV_GET(ac1, 1)
    xa += 2 * X_CH;
    {
      const uint32_t mo = sb + OFF_MODV + (16 + (cidx & 1) * 4 + wg + 2 * round) * 4;
      ga2 = lds32(mo);
      const uint32_t dsk2 = lds32(mo + 32);
#pragma unroll
      for (int pp = 0; pp < 2; pp++) {
        ldsm4t(ha + pp * 1024, hv[pp][0], hv[pp][1], hv[pp][2], hv[pp][3]); ldsm4t(xa + pp * 2048, xv[pp][0], xv[pp][1], xv[pp][2], xv[pp][3]);
#pragma unroll
        for (int m = 0; m < 4; m++) hv[pp][m] = bf2_mul(hv[pp][m], dsk2);
      }
      ha += 2 * H_CH;
    }
    CONV_FIN(0, 0) CONV_FIN(0, 1) CONV_FIN(0, 2) CONV_FIN(0, 3)
    stsm4t(xa, xv[0][0], xv[0][1], xv[0][2], xv[0][3]);
    wg_wait<0>();
    CONV_MOVE(ac3, ac2, 16)
    CONV_MMA(wgmma_rs32, ac3, wb, 3)
    CONV_PUT(ac2, 2)
    bar_sync(BAR_WG0 + wg, 128);
    kt += 2 * KTAB_CH;
    if (wg == 0) { CONV_LOAD(wa, 0) }
    CONV_GET(ac2, 2)
    CONV_FIN(1, 0) CONV_FIN(1, 1)
    wg_wait<0>();
    CONV_PUT(ac3, 3)
    if (wg == 1) {
      if (round == 0) bar_sync(BAR_K3, 256);
      CONV_LOAD(wa, 0)
    }
#pragma unroll
    for (int e = 0; e < 4; e++) asm volatile("add.f32 %0, %1, 0f00000000;" : "=f"(y[3][e]) : "f"(ac3[e]));
  }
  CONV_TAIL(1)
  if (wg == 0) bar_sync(BAR_PP0, 256);
#undef CONV_LOAD
#undef CONV_MMA
#undef CONV_MOVE
#undef CONV_PUT
#undef CONV_GET
#undef CONV_FIN
#undef CONV_TAIL
}

__global__ void __cluster_dims__(2, 1, 1) __launch_bounds__(NTHREADS, 1)
fused_block_kernel(const __grid_constant__ Params p, const __grid_constant__ Maps tm) {
  extern __shared__ __align__(1024) unsigned char smem_raw[];
  const uint32_t sb = s2u(smem_raw);
  const int tid = threadIdx.x, lane = tid & 31;
  const int warp = __shfl_sync(0xffffffffu, tid >> 5, 0);
  const int wg = warp >> 2, tw = tid & 127;
  const int bid = blockIdx.x;
  const uint32_t rank = bid & 1;
  const int cl = bid >> 1;
  const bool is_conv = bid < NCONV;
  const uint32_t fullX = sb + OFF_PUB + 72, freeX = sb + OFF_PUB + 104;
  const uint32_t fullA = sb + OFF_BAR, emptyA = fullA + 8 * NA, fullB = emptyA + 8 * NA, emptyB = fullB + 8 * NB2;
  const uint32_t fullG = emptyB + 8 * NB2, emptyG = fullG + 80;
  {
    const uint32_t v = reinterpret_cast<const uint32_t*>(&p)[(lane & 1) * 16 + (tid >> 10)];
    asm volatile("" ::"r"(v));
  }
  uint32_t rv[2][7];
  GenParams gp;
  if (wg < 2) {
    const uint32_t* xr = (const uint32_t*)(p.x + (size_t)(16 * bid + 2 * warp) * DM) + lane;
#pragma unroll
    for (int r = 0; r < 2; r++)
#pragma unroll
      for (int k = 0; k < 7; k++) rv[r][k] = __ldg(xr + r * (DM / 2) + 32 * k);
  }
  uint32_t cv[4], dsk;
  if (wg == 2) {
#pragma unroll
    for (int u = 0; u < 4; u++) cv[u] = __ldg(reinterpret_cast<const unsigned short*>(p.cvec) + min(tw + 128 * u, DM - 1));
    dsk = __ldg(reinterpret_cast<const unsigned short*>(p.dskip) + min(8 * cl + (tw & 7), DM - 1));
  }
  uint32_t ep;
  asm volatile("ld.global.u32 %0, [%1];" : "=r"(ep) : "l"(&p.s->epoch[bid] + (tid & p.zero)));
  if (is_conv && wg == 2) gp = load_gen_params(p, 4 * bid, tw);
  if (warp == 8) {
    if (elect()) {
      if (sb & 1023) __trap();
#pragma unroll
      for (int u = 0; u < 7; u++) asm volatile("prefetch.tensormap [%0];" ::"l"(&tm.wsp + u) : "memory");
      for (int s = 0; s < NA; s++) { mbar_init(fullA + 8 * s, 1); mbar_init(emptyA + 8 * s, 4); }
      for (int s = 0; s < NB2; s++) { mbar_init(fullB + 8 * s, 1); mbar_init(emptyB + 8 * s, 2); }
      for (int s = 0; s < 8; s++) mbar_init(sb + OFF_PUB + 8 * s, (is_conv || s) ? 4 : 1);
      for (int s = 8; s < 16; s++) mbar_init(sb + OFF_PUB + 8 * s, s == 13 || s == 14 ? 4 : 1);
      for (int s = 0; s < 16; s++) mbar_init(fullG + 8 * s, s < 10 || s >= 14 ? 1 : s < 13 ? 4 : 3);
      mbar_expect(emptyG + 32, 512); mbar_expect(emptyG + 40, 4);
      asm volatile("fence.mbarrier_init.release.cluster;" ::: "memory");
      fence_async_smem();
      if (is_conv) {
        mbar_expect(sb + OFF_PUB + 64, 21504);
#pragma unroll 1
        for (int u = 0; u < 6; u++) tma2d(sb + OFF_MODW + u * 3584, &tm.wmod8, (u >> 1) * DM + 8 * cl, (u & 1) * 224, sb + OFF_PUB + 64);
      } else {
        const int a = bid - NCONV;
        mbar_expect(sb + OFF_PUB + 64, 50176);
        tma2d(sb + OFF_G1, &tm.wmod, 3 * DM + 56 * a, 0, sb + OFF_PUB + 64); tma2d(sb + OFF_G1 + 25088, &tm.wmod, 3 * DM + 56 * a, 224, sb + OFF_PUB + 64);
      }
    }
    __syncwarp();
  }
  asm volatile("barrier.cluster.arrive.relaxed.aligned;" ::: "memory");
  ep = __shfl_sync(0xffffffffu, ep, 0) + 1;
  if (wg < 2) ln1_publish(p, gp, &tm.nx, rv, sb, bid, tid);
  if (wg == 2) {
#pragma unroll
    for (int u = 0; u < 4; u++) {
      const float x = __uint_as_float(cv[u] << 16);
      const uint32_t y = pack_bf16(__fdividef(x, 1.f + __expf(-x)), 0.f);
      asm volatile("st.shared.u16 [%0], %1;" ::"r"(sb + OFF_SCB + (tw + 128 * u) * 2), "h"((unsigned short)y) : "memory");
    }
    if (tw < 8) sts32(sb + OFF_MODV + (24 + tw) * 4, __byte_perm(dsk, dsk, 0x1010));
  }
  uint4 nx[2][4];
#pragma unroll 1
  for (int it = 0; it < (wg == 2 ? 2 : (int)is_conv); it++) {
    if (is_conv) gen_kernel(p, gp, sb + (wg == 2 ? OFF_GEN2 : OFF_GEN01 + wg * 4 * GEN_BYTES), sb + OFF_KTAB + (2 - wg + 3 * it) * KTAB_CH, tw, BAR_WG0 + wg,
                            tid == 0 ? p.s->cnt_nx : nullptr, wg == 2 && it == 0 ? 4 * bid + 3 : -1,
                            wg < 2 ? p.s->nx + (size_t)(4 * bid + wg) * (SEQ / 4) + tw : nullptr, ep * NCTA, nx);
    if (wg == 2 && (it == 0 || (!is_conv && bid < NCONV + 8))) {
      const int wp = warp & 3, g = lane >> 2, c = lane & 3;
      bar_sync(BAR_WG2, 128);
      uint32_t sc[14];
#pragma unroll
      for (int u = 0; u < 14; u++) sc[u] = lds32(sb + OFF_SCB + (112 * wp + 8 * u + 2 * c) * 2);
      const uint32_t pitch = is_conv ? 16 : 112, ts = is_conv ? 7168 : 16;
      uint32_t wa = sb + (is_conv ? OFF_MODW : OFF_G1) + (112 * wp + (lane & 7) + (lane >> 4) * 8) * pitch + ((lane >> 3) & 1) * ts;
      mbar_wait(sb + OFF_PUB + 64, it);
#pragma unroll 1
      for (int i = 0; i < (is_conv ? 2 : 4); i++) {
        uint32_t w[7][4];
#pragma unroll
        for (int ks = 0; ks < 7; ks++) ldsm4t(wa + ks * 16 * pitch, w[ks][0], w[ks][1], w[ks][2], w[ks][3]);
        float m[4] = {0.f, 0.f, 0.f, 0.f};
#pragma unroll
        for (int ks = 0; ks < 7; ks++) mma16816_bf(m, w[ks][0], w[ks][1], w[ks][2], w[ks][3], sc[2 * ks], sc[2 * ks + 1]);
        if (c < 2) stsf(sb + OFF_MODP + (wp * 64 + 16 * i + 8 * c + g) * 4, c ? m[2] : m[0]);
        wa += 2 * ts;
      }
      bar_sync(BAR_WG2, 128);
      if (tw < 56) {
        const float v = round_bf16((ldsf(sb + OFF_MODP + tw * 4) + ldsf(sb + OFF_MODP + (64 + tw) * 4)) + (ldsf(sb + OFF_MODP + (128 + tw) * 4) + ldsf(sb + OFF_MODP + (192 + tw) * 4)));
        if (!is_conv) st_rlx2(&p.s->modw[(3 + 2 * it) * DM + 56 * (bid - NCONV) + tw], __float_as_uint(v), ep);
        else if (tw < 24) sts32(sb + OFF_MODV + tw * 4, dup_bf16((tw >> 3) == 1 ? 1.f + v : v));
      }
      if (is_conv) bar_arrive(BAR_SC, 384);
      else if (warp == 11 && it == 0 && bid < NCONV + 8 && elect()) {
        mbar_expect(sb + OFF_PUB + 64, 50176);
        tma2d(sb + OFF_G1, &tm.wmod, 5 * DM + 56 * (bid - NCONV), 0, sb + OFF_PUB + 64); tma2d(sb + OFF_G1 + 25088, &tm.wmod, 5 * DM + 56 * (bid - NCONV), 224, sb + OFF_PUB + 64);
      }
      __syncwarp();
    }
    if (wg == 2 && is_conv) {
      if (it == 1) bar_arrive(BAR_K3, 256);
      bar_sync(BAR_WG2, 128);
    }
  }
  asm volatile("barrier.cluster.wait.aligned;" ::: "memory");

  if (wg == 2) {
    asm volatile("setmaxnreg.dec.sync.aligned.u32 56;");
    const int lane = fresh_tid() & 31;
    if (!is_conv) {
      bar_sync(BAR_AUX, 384);
      if (warp == 10 && elect()) {
#pragma unroll
        for (int u = 0; u < 4; u++) prefetch_l2(p.w_sp + (size_t)bid * 32768 + u * 8192, 16384);
        prefetch_l2(p.w_out + (size_t)bid * 3136, 6272);
      }
    }
    if (warp == 11 && rank == 0 && lane == 0) {
      uint32_t sm; asm volatile("mov.u32 %0, %%smid;" : "=r"(sm));
      sm >>= 1;
      uint32_t id = sm < 32 ? (sm & 7) * 8 + (sm >> 3) : sm < 60 ? ((sm - 32) % 7 + 1) * 8 + 4 + (sm - 32) / 7 : 4 + (sm & 3);
#pragma unroll 1
      for (int it = 0; it < 64 && atomicExch(&p.s->claim[id], ep) == ep; it++) id = (id + 1) & 63;
#pragma unroll
      for (int r = 0; r < 2; r++)
        asm volatile("{.reg .b32 a, m; mapa.shared::cluster.u32 a, %0, %1; mapa.shared::cluster.u32 m, %3, %1;\n"
                     "st.async.weak.shared::cluster.mbarrier::complete_tx::bytes.b32 [a], %2, [m];}" ::"r"(sb + OFF_LID), "r"(r), "r"(id), "r"(emptyG + 40) : "memory");
    }
    __syncwarp();
    mbar_wait(emptyG + 40, 0);
    const int lid = __shfl_sync(0xffffffffu, lds32(sb + OFF_LID), 0), ti = (lid >> 5) * 8 + (lid & 7), tj = ((lid >> 3) & 3) * 2 + (int)rank;
    if (warp == 8) {
      int slot = 0; uint32_t ph = 0, ready = 0;
      const bool el = elect();
#pragma unroll 1
      for (int q = 0; q < 4; q++) {
        if (q < 2) mbar_wait(freeX + 8 * q, 0);
        wait_ready(ready, q, p.s->cnt_x1, 32, 4, ep * NCONV, lane);
        if (el) {
          mbar_expect(fullX + 8 * q, 28672);
          bulk_g2s_mc(sb + OFF_A + q * 28672 + rank * 14336, (const char*)p.s->x1 + (size_t)(ti * 8 + q * 2 + rank) * 14336, 14336, fullX + 8 * q);
        }
      }
#pragma unroll 1
      for (int u = 0; u < 32; u++) {
        mbar_wait(emptyA + 8 * slot, ph);
        if (el) {
          mbar_expect(fullA + 8 * slot, 16384);
          tma2d_mc(sb + OFF_A + slot * A_SLOT + rank * 8192, &tm.wsp, (u < 2 ? 2 * ti + u : k_order(u, ti)) * 64, ti * 128 + (int)rank * 64, fullA + 8 * slot);
        }
        if (++slot == NA) { slot = 0; ph ^= 1; }
      }
      ready = 0;
      mbar_wait(emptyA + 8 * 3, 1);
#pragma unroll 1
      for (int u = 0; u < 7; u++) {
        const int v = u - (u > 3), bf = u == 3 ? 4 : v & 3, jj = u == 3 ? tj ^ 1 : ((tj & 6) + 2 + v) & 7;
        if (u == 3 || u >= 5) mbar_wait(emptyG + 8 * (u == 3 ? 3 : bf), 0);
        if (el) { mbar_expect(fullG + 16 * bf, 14336); mbar_expect(fullG + 16 * bf + 8, 14336); }
#pragma unroll 1
        for (int h = u == 3 ? 0 : rank; h <= (u == 3 ? 1 : rank); h++) {
          wait_ready(ready, 2 * jj + h, p.s->flag_gt + ti * 16 * FS, FS, 16, ep, lane);
          if (el) {
            const char* src = (const char*)p.s->gt + (size_t)((ti * 8 + jj) * 2 + h) * 14336;
            if (u == 3) bulk_g2s(sb + OFF_STG + h * 14336, src, 14336, fullG + 64 + 8 * h);
            else bulk_g2s_mc(sb + OFF_A + bf * 28672 + h * 14336, src, 14336, fullG + 16 * bf + 8 * h);
          }
        }
      }
    } else if (warp == 9) {
      int slot = 4; uint32_t ph = 0x1f, ready = 0;
      const bool el = elect();
#pragma unroll 1
      for (int b = 0; b < 16; b++) {
        { mbar_wait(emptyB + 8 * slot, (ph >> slot) & 1); ph ^= 1u << slot; }
        wait_ready(ready, b, p.s->flag_wp + tj * 32, 1, 16, ep, lane);
        if (el) {
          const uint32_t n = (b & 1) ? 10752 : 14336;
          mbar_expect(fullB + 8 * slot, n);
          bulk_g2s(sb + OFF_B + slot * B_SLOT, (const char*)p.s->wp + (size_t)(tj + (b & 8)) * 100352 + ((b >> 1) & 3) * 25088 + (b & 1) * 14336, n, fullB + 8 * slot);
        }
        if (++slot == NB) slot = 0;
      }
      ready = 0;
#pragma unroll 1
      for (int u = 2; u < 32; u++) {
        const int kk = k_order(u, ti);
        { mbar_wait(emptyB + 8 * slot, (ph >> slot) & 1); ph ^= 1u << slot; }
        if (u == 7) mbar_wait(sb + OFF_PUB + 120, 0);
        wait_ready(ready, kk, p.s->flag_z2 + tj * 32 * FS, FS, 32, ep, lane);
        if (el) {
          mbar_expect(fullB + 8 * slot, B_SLOT);
          bulk_g2s(sb + OFF_B + slot * B_SLOT, (const char*)p.s->z2 + (size_t)(tj * 32 + kk) * B_SLOT, B_SLOT, fullB + 8 * slot);
        }
        if (++slot == NB2) slot = 0;
      }
#pragma unroll 1
      for (int u = 0; u < 8; u++) {
        const int jj = (u & 3) == 0 ? tj ^ (u >> 2) : ((tj & 6) + 1 + u - (u > 4)) & 7;
        mbar_wait(emptyB + 8 * slot, (ph >> slot) & 1); ph ^= 1u << slot;
        if (el) {
          mbar_expect(fullB + 8 * slot, B_SLOT);
          tma2d(sb + OFF_B + slot * B_SLOT, &tm.wout, tj * 56, jj * 112, fullB + 8 * slot);
        }
        if (++slot == NB) slot = 0;
      }
    } else {
      const int w = warp - 10;
      const uint32_t pb = sb + OFF_PUB + w * 32;
      if (is_conv) {
#pragma unroll 1
        for (int round = 0; round < 2; round++) {
          mbar_wait(pb + round * 8, 0);
          if (elect()) {
            const int q = 2 * round + w;
            asm volatile("cp.async.bulk.tensor.5d.global.shared::cta.bulk_group [%0, {%1, %2, %3, %4, %5}], [%6];" ::"l"(&tm.x1), "r"(0), "r"(bid), "r"(0), "r"(q), "r"(0),
                         "r"(sb + OFF_X + q * X_CH) : "memory");
            asm volatile("cp.async.bulk.commit_group;" ::: "memory");
            asm volatile("cp.async.bulk.wait_group 0;" ::: "memory");
            red_rlx(&p.s->cnt_x1[q * 32], 1u);
          }
          __syncwarp();
        }
      }
      {
        uint4 v[5];
        unsigned it = 0;
        bool ok;
        do {
          ok = true;
#pragma unroll
          for (int u = 0; u < 5; u++) {
            const int i = lane + 32 * u;
            v[u] = ld_rlx4(i < 112 ? &p.s->csb[(8 * w + tj) * 112 + i] : reinterpret_cast<const uint4*>(&p.s->modw[5 * DM + 56 * tj + 2 * min(i - 112, 27)]));
            ok = ok && v[u].y == ep && v[u].w == ep;
          }
        } while (!ok && ++it < SPIN_LIMIT);
#pragma unroll
        for (int u = 0; u < 5; u++) {
          const int i = lane + 32 * u;
          if (i < 140) sts64(sb + OFF_CSB + w * X_CH + i * 8, i < 112 ? v[u].x : __byte_perm(v[u].x, v[u].z, 0x7632), v[u].z);
        }
        __syncwarp();
        bar_arrive(BAR_TAB, 320);
      }
      if (w == 0) {
#pragma unroll 1
        for (int ph = 0; ph < 2; ph++) {
          char* dst = ph ? (char*)p.s->gt + (size_t)(ti * 8 + tj) * 28672 : (char*)p.s->z2 + (size_t)(tj * 32 + 2 * ti) * B_SLOT;
          uint32_t* fl = ph ? &p.s->flag_gt[(ti * 16 + tj * 2) * FS] : &p.s->flag_z2[(tj * 32 + 2 * ti) * FS];
          const bool el = elect();
#pragma unroll
          for (int h = 0; h < 2; h++) {
            mbar_wait(sb + OFF_PUB + h * 32 + 16 + ph * 8, 0);
            if (el) {
              asm volatile("cp.async.bulk.global.shared::cta.bulk_group [%0], [%1], %2;" ::"l"(dst + h * B_SLOT), "r"(sb + OFF_STG + h * B_SLOT), "r"(B_SLOT) : "memory");
              asm volatile("cp.async.bulk.commit_group;" ::: "memory");
            }
          }
          if (el) {
            asm volatile("cp.async.bulk.wait_group 1;" ::: "memory");
            st_rlx(fl, ep);
            asm volatile("cp.async.bulk.wait_group 0;" ::: "memory");
            st_rlx(fl + FS, ep);
            mbar_arrive(ph ? emptyG + 24 : sb + OFF_PUB + 120);
          }
          __syncwarp();
        }
      }
    }
    __syncwarp();
    asm volatile("barrier.cluster.arrive.relaxed.aligned;" ::: "memory");
    asm volatile("barrier.cluster.wait.aligned;" ::: "memory");
  } else {
    if (is_conv) {
      bar_sync(BAR_SC, 384);
      {
        if (tw < 32) sts128(sb + OFF_H + (wg + (tw >> 4) * 2) * H_CH + ((tw >> 3) & 1) * H_HI + (tw & 7) * 16, 0, 0, 0, 0);
        const uint32_t ho = sb + OFF_H + wg * H_CH + ((tw >> 1) & 1) * H_HI + (8 + (tw >> 2)) * 16 + (tw & 1) * 8;
        const uint32_t xo = sb + OFF_X + wg * X_CH + (tw >> 4) * 128 + (tw & 1) * 8;
#pragma unroll
        for (int r = 0; r < 2; r++) {
          const uint32_t mo = sb + OFF_MODV + (rank * 4 + wg + 2 * r) * 4;
          const uint32_t sa2 = lds32(mo), ca1 = lds32(mo + 32);
#pragma unroll
          for (int u = 0; u < 4; u++) {
            const uint4 a = nx[r][u];
            sts64(ho + r * 2 * H_CH + u * 512, bf2_add(bf2_mul(__byte_perm(a.x, a.y, 0x5410), ca1), sa2), bf2_add(bf2_mul(__byte_perm(a.z, a.w, 0x5410), ca1), sa2));
            sts64(xo + r * 2 * X_CH + u * 1024 + ((((tw >> 1) & 7) ^ (bid & 7)) * 16), __byte_perm(a.x, a.y, 0x7632), __byte_perm(a.z, a.w, 0x7632));
          }
        }
        fence_async_smem();
        bar_sync(BAR_WG0 + wg, 128);
        if (tw < 2) mbar_arrive_cluster(freeX, tw);
        if (tid == 32) {
#pragma unroll
          for (int u = 0; u < 4; u++) prefetch_l2(p.w_sp + (size_t)bid * 32768 + u * 8192, 16384);
          prefetch_l2(p.w_out + (size_t)bid * 3136, 6272);
        }
      }
      __syncwarp();
      bar_sync(BAR_MMA, 384);
      conv_channels(p, sb, bid, tw, wg);
      bar_sync(BAR_WG0 + wg, 128);
      const int t2 = fresh_tid() & 127;
      if (t2 < 2) mbar_arrive_cluster(freeX + 8, t2);
    } else {
      const int a = bid - NCONV, g = lane >> 2, c = lane & 3;
      if (warp == 0) {
        if (lane == 0) {
          asm volatile("cp.async.bulk.wait_group 0;" ::: "memory");
          red_rlx(p.s->cnt_nx, 1u);
        }
        __syncwarp();
        if (elect()) {
          mbar_expect(sb + OFF_PUB, 100352);
#pragma unroll 1
          for (int q = 0; q < 4; q++) tma2d(sb + OFF_WIN + q * 25088, &tm.win, q * FF + (a < 8 ? FH : 0) + 112 * (a & 7), 0, sb + OFF_PUB);
        }
        __syncwarp();
      }
      if (tid < 224) {
        const int k = 2 * tid, q = k / NCONV;
        const uint2* mw = &p.s->modw[3 * DM + 4 * (k - q * NCONV) + q];
        uint2 v[4];
        unsigned it = 0;
        for (;;) {
#pragma unroll
          for (int u = 0; u < 4; u++) v[u] = ld_rlx2(mw + (u >> 1) * DM + (u & 1) * 4);
          if ((v[0].y == ep && v[1].y == ep && v[2].y == ep && v[3].y == ep) || ++it >= SPIN_LIMIT) break;
          __nanosleep(100);
        }
        sts64(sb + OFF_AUXS + tid * 8, pack_bf16(1.f + __uint_as_float(v[2].x), 1.f + __uint_as_float(v[3].x)), __byte_perm(v[0].x, v[1].x, 0x7632));
      }
      mbar_wait(sb + OFF_PUB, 0);
      bar_sync(BAR_CONS, 256);
      {
        float cs[7][4], bi[7][4];
#pragma unroll
        for (int u = 0; u < 7; u++)
#pragma unroll
          for (int e = 0; e < 4; e++) { cs[u][e] = 0.f; bi[u][e] = 0.f; }
        const int ks0 = (warp >> 1) * 7 + (warp & 1) * 4;
        const uint32_t src = sb + OFF_WIN + ((lane & 7) + (lane >> 4) * 8) * 224 + ((lane >> 3) & 1) * 16;
        const uint32_t dst = sb + OFF_WIN + (lane >> 4) * 1792 + (lane & 15) * 16;
#pragma unroll 1
        for (int ks = ks0; ks < ks0 + 4 - (warp & 1); ks++) {
          uint32_t w[7][4];
#pragma unroll
          for (int u = 0; u < 7; u++) ldsm4t(src + ks * 3584 + u * 32, w[u][0], w[u][1], w[u][2], w[u][3]);
          const float2 t0 = lds2f(sb + OFF_AUXS + (8 * ks + c) * 8), t1 = lds2f(sb + OFF_AUXS + (8 * ks + 4 + c) * 8);
          __syncwarp();
#pragma unroll
          for (int u = 0; u < 7; u++) {
            mma16816_bf(bi[u], w[u][0], w[u][1], w[u][2], w[u][3], __float_as_uint(t0.y), __float_as_uint(t1.y));
            w[u][0] = bf2_mul(w[u][0], __float_as_uint(t0.x)); w[u][1] = bf2_mul(w[u][1], __float_as_uint(t0.x));
            w[u][2] = bf2_mul(w[u][2], __float_as_uint(t1.x)); w[u][3] = bf2_mul(w[u][3], __float_as_uint(t1.x));
            mma16816_bf(cs[u], w[u][0], w[u][1], w[u][2], w[u][3], 0x3f803f80u, 0x3f803f80u);
            stsm4(dst + ks * 3584 + u * 256, w[u][0], w[u][1], w[u][2], w[u][3]);
          }
        }
        fence_async_smem();
        __syncwarp();
        if (elect()) {
          asm volatile("cp.async.bulk.global.shared::cta.bulk_group [%0], [%1], %2;" ::"l"((char*)p.s->wp + (size_t)a * 100352 + ks0 * 3584), "r"(sb + OFF_WIN + ks0 * 3584),
                       "r"((4 - (warp & 1)) * 3584) : "memory");
          asm volatile("cp.async.bulk.commit_group;" ::: "memory");
        }
        if (c < 2) {
#pragma unroll
          for (int u = 0; u < 7; u++) sts2f(sb + OFF_AUXR + (warp * 112 + 16 * u + 8 * c + g) * 8, c ? cs[u][2] : cs[u][0], c ? bi[u][2] : bi[u][0]);
        }
        bar_sync(BAR_CONS, 256);
        if (tid < 112) {
          float s = 0.f, t = 0.f;
#pragma unroll
          for (int u = 0; u < 8; u++) { const float2 v = lds2f(sb + OFF_AUXR + (u * 112 + tid) * 8); s += v.x; t += v.y; }
          st_rlx4(&p.s->csb[a * 112 + tid], __float_as_uint(0.5f * s), ep, __float_as_uint(0.5f * t), ep);
        }
        __syncwarp();
        if (elect()) {
          asm volatile("cp.async.bulk.wait_group 0;" ::: "memory");
          st_rlx(&p.s->flag_wp[(a & 7) * 32 + (a >> 3) * 8 + warp], ep);
        }
        bar_sync(BAR_CONS, 256);
      }
      bar_sync(BAR_AUX, 384);
      if (tw < 4) mbar_arrive_cluster(freeX + 8 * (tw >> 1), tw & 1);
    }

    asm volatile("setmaxnreg.inc.sync.aligned.u32 224;");
    {
    const int tid = fresh_tid(), lane = tid & 31, tw = tid & 127;
    const int wp = warp & 3, g = lane >> 2, c = lane & 3;
    int lid = 0, ti, tj;
    uint32_t bspr0, bspr1;
    float acc2[56], acc1[56];
    int bs = 4; uint32_t bph = 0;
    int rel = 4;
    auto release_bn = [&](int nb) { if (tw == 0) mbar_arrive(emptyB + 8 * rel); if (++rel == nb) rel = 0; };
    auto next_bn = [&](int nb) {
      mbar_wait(fullB + 8 * bs, (bph >> bs) & 1);
      bph ^= 1u << bs;
      const uint32_t o = sb + OFF_B + bs * B_SLOT;
      if (++bs == nb) bs = 0;
      return o;
    };
    auto release_b = [&]() { release_bn(NB); };
    auto next_b = [&]() { return desc_lo(next_bn(NB), 1792); };
    auto issue_z1 = [&](int u, int odd) {
      const uint32_t db = next_b(), da = desc_lo(sb + OFF_A + (u >> 1) * 28672 + wg * 14336 + odd * 8192, 16);
      wg_fence();
#pragma unroll
      for (int k = 0; k < 4 - odd; k++) wgmma_n112_tA<HI_SW128, HI_NOSW>(acc1, da + 128 * k, db + 224 * k, (u | k) != 0);
      wg_commit();
    };
    auto release_a = [&](int s0, int n) { if (tw < 2 * n) mbar_arrive_cluster(emptyA + 8 * (s0 + (tw >> 1)), tw & 1); };
    uint32_t xres[4][4], z1[28];
    float ra[2], rb[2];
    {
      float sum = 0.f, sq = 0.f;
      uint32_t a0[4][4], a1[3][4];
      uint32_t aa = sb + OFF_A + wg * 14336 + ((lane & 7) + (lane >> 4) * 8) * 128 + (((2 * wp + ((lane >> 3) & 1)) ^ (lane & 7)) * 16);
#define G1_STAT1(A, N, R) _Pragma("unroll") for (int k = 0; k < N; k++) _Pragma("unroll") for (int e = R; e < 4; e += 2) {  \
        const float lo = bf_lo(A[k][e]), hi = bf_hi(A[k][e]);                                                             \
        sum += lo + hi; sq = fmaf(lo, lo, fmaf(hi, hi, sq)); }
#define G1_STATS(A, N) if (rank) { G1_STAT1(A, N, 1) } else { G1_STAT1(A, N, 0) }                                          \
        asm volatile("" : "+f"(sum), "+f"(sq));
      mbar_wait(fullX, 0);
#pragma unroll
      for (int k = 0; k < 4; k++) ldsm4t(aa + k * 2048, a0[k][0], a0[k][1], a0[k][2], a0[k][3]);
#pragma unroll 1
      for (int q = 0; q < 4; q++) {
        const int b1 = bs + 1 == NB ? 0 : bs + 1;
        mbar_wait2(fullB + 8 * bs, (bph >> bs) & 1, fullB + 8 * b1, (bph >> b1) & 1);
        bph ^= (1u << bs) | (1u << b1);
        uint32_t db = desc_lo(sb + OFF_B + bs * B_SLOT, 1792);
        bs = b1 + 1 == NB ? 0 : b1 + 1;
        wg_fence();
#pragma unroll
        for (int k = 0; k < 4; k++) wgmma_rs112<HI_NOSW>(acc2, a0[k][0], a0[k][1], a0[k][2], a0[k][3], db + 224 * k, (q | k) != 0);
        wg_commit();
        wg_wait<1>();
        if (q > 0) release_b();
        else { mbar_wait(emptyG + 40, 0); lid = lds32(sb + OFF_LID); }
#pragma unroll
        for (int k = 0; k < 3; k++) ldsm4t(aa + (4 + k) * 2048, a1[k][0], a1[k][1], a1[k][2], a1[k][3]);
        G1_STATS(a0, 4)
        db = desc_lo(sb + OFF_B + b1 * B_SLOT, 1792);
        wg_fence();
#pragma unroll
        for (int k = 0; k < 3; k++) wgmma_rs112<HI_NOSW>(acc2, a1[k][0], a1[k][1], a1[k][2], a1[k][3], db + 224 * k, 1);
        wg_commit();
        wg_wait<1>();
        release_b();
        aa += 28672;
        if (q < 3) mbar_wait(fullX + 8 * (q + 1), 0);
#pragma unroll
        for (int k = 0; k < 4; k++) ldsm4t(aa + k * 2048, a0[k][0], a0[k][1], a0[k][2], a0[k][3]);
        G1_STATS(a1, 3)
      }
#undef G1_STAT1
#undef G1_STATS
      lid = __shfl_sync(0xffffffffu, lid, 0);
      ti = (lid >> 5) * 8 + (lid & 7); tj = ((lid >> 3) & 3) * 2 + (int)rank;
      bspr0 = __ldg(reinterpret_cast<const unsigned short*>(p.b_sp) + ti * 128 + 64 * wg + 16 * wp + g);
      bspr1 = __ldg(reinterpret_cast<const unsigned short*>(p.b_sp) + ti * 128 + 64 * wg + 16 * wp + g + 8);
#pragma unroll
      for (int o = 1; o < 4; o <<= 1) { sum += __shfl_xor_sync(0xffffffffu, sum, o); sq += __shfl_xor_sync(0xffffffffu, sq, o); }
      const float mean = sum * (1.f / DM), rs = rsqrtf(fmaxf(sq * (1.f / DM) - mean * mean, 0.f) + 1e-5f);
      const float rr = 0.5f * rs, rm = -rs * mean;
      const uint32_t so = sb + OFF_X + 2 * X_CH + (warp * 8 + g) * 8;
      if (c == 0) asm volatile("{.reg .b32 r, m; mapa.shared::cluster.u32 r, %0, %1; mapa.shared::cluster.u32 m, %4, %1;\n"
                               "st.async.weak.shared::cluster.mbarrier::complete_tx::bytes.v2.f32 [r], {%2, %3}, [m];}" ::"r"(so), "r"(rank ^ 1), "f"(rr), "f"(rm), "r"(emptyG + 32) : "memory");
#pragma unroll
      for (int u = 0; u < 4; u++) {
        const int bb = 14 * tj + 8 * (u >> 1) + (lane & 7);
        ldsm4t(sb + OFF_A + (lane >> 3) * 28672 + wg * 14336 + bb * 128 + (((2 * wp + (u & 1)) ^ (bb & 7)) * 16), xres[u][0], xres[u][1], xres[u][2], xres[u][3]);
      }
      bar_sync(BAR_TAB, 320);
      mbar_wait(emptyG + 32, 0);
      const float2 ot = lds2f(so);
      const float r2 = rank ? ot.x : rr, m2 = rank ? ot.y : rm, r3 = rank ? rr : ot.x, m3 = rank ? rm : ot.y;
      ra[0] = r2; rb[0] = m2; ra[1] = r3; rb[1] = m3;
    }
    issue_z1(0, 0);
    wg_wait<1>();
    release_b();
    int as = 0; uint32_t aph = 0;
    auto mma_g2 = [&](int u) {
      uint32_t db;
      if (u < 2) { mbar_wait(sb + OFF_PUB + u * 32 + 16, 0); db = desc_lo(sb + OFF_STG + u * B_SLOT, 1792); }
      else db = desc_lo(next_bn(NB2), 1792);
      mbar_wait(fullA + 8 * as, aph);
      const uint32_t da = desc_lo(sb + OFF_A + as * A_SLOT + wg * 8192, 16);
      wg_fence();
#pragma unroll
      for (int k = 0; k < 4; k++) wgmma_n112<HI_SW128, HI_NOSW>(acc1, da + 2 * k, db + 224 * k, (u | k) != 0);
      wg_commit();
    };
#pragma unroll 1
    for (int hf = 0;; hf++) {
      float s0 = 0.f, q0 = 0.f, s1 = 0.f, q1 = 0.f;
      const uint32_t cbo = sb + OFF_CSB + hf * X_CH + c * 16;
      float4 cbn[2] = {lds4f(cbo), lds4f(cbo + 64)};
#pragma unroll
      for (int h = 0; h < 7; h++) {
        const float4 cb[2] = {cbn[0], cbn[1]};
        if (h < 6) { cbn[0] = lds4f(cbo + h * 128 + 128); cbn[1] = lds4f(cbo + h * 128 + 192); }
        if (h % 3 == 0 && h < 6 && hf == 1) { mma_g2(h / 3); as++; }
#pragma unroll
        for (int e = 0; e < 2; e++) {
          float* a = acc2 + 8 * h + 4 * e;
          a[0] = gelu_half(fmaf(ra[0], a[0], fmaf(rb[0], cb[e].x, cb[e].y))); a[1] = gelu_half(fmaf(ra[0], a[1], fmaf(rb[0], cb[e].z, cb[e].w)));
          a[2] = gelu_half(fmaf(ra[1], a[2], fmaf(rb[1], cb[e].x, cb[e].y))); a[3] = gelu_half(fmaf(ra[1], a[3], fmaf(rb[1], cb[e].z, cb[e].w)));
          s0 += a[0] + a[1]; q0 = fmaf(a[0], a[0], fmaf(a[1], a[1], q0));
          s1 += a[2] + a[3]; q1 = fmaf(a[2], a[2], fmaf(a[3], a[3], q1));
        }
        asm volatile("" : "+f"(s0), "+f"(q0), "+f"(s1), "+f"(q1));
      }
      if (hf == 1) break;
      {
#pragma unroll
        for (int o = 1; o < 4; o <<= 1) {
          s0 += __shfl_xor_sync(0xffffffffu, s0, o); q0 += __shfl_xor_sync(0xffffffffu, q0, o);
          s1 += __shfl_xor_sync(0xffffffffu, s1, o); q1 += __shfl_xor_sync(0xffffffffu, q1, o);
        }
        const int row = 64 * wg + 16 * wp + g;
        if (c < 2) st_rlx4(&p.s->st3[(ti * 8 + tj) * 128 + row + 8 * c], __float_as_uint(c ? s1 : s0), ep, __float_as_uint(c ? q1 : q0), ep);
        wg_wait<0>();
        release_b();
        issue_z1(1, 1); issue_z1(2, 0); issue_z1(3, 1);
        wg_wait<2>();
        release_b();
        release_a(0, 1);
        uint4 st[4];
        unsigned it = 0;
        bool ok;
        do {
#pragma unroll
          for (int u = 0; u < 4; u++) st[u] = ld_rlx4(&p.s->st3[(ti * 8 + c + 4 * (u & 1)) * 128 + row + 8 * (u >> 1)]);
          ok = true;
#pragma unroll
          for (int u = 0; u < 4; u++) ok = ok && st[u].y == ep && st[u].w == ep;
          ok = __all_sync(0xffffffffu, ok);
        } while (!ok && ++it < SPIN_LIMIT);
        __syncwarp();
        wg_wait<0>();
        release_b(); release_b();
        release_a(1, 2);
        s0 = __uint_as_float(st[0].x) + __uint_as_float(st[1].x); q0 = __uint_as_float(st[0].z) + __uint_as_float(st[1].z);
        s1 = __uint_as_float(st[2].x) + __uint_as_float(st[3].x); q1 = __uint_as_float(st[2].z) + __uint_as_float(st[3].z);
#pragma unroll
        for (int o = 1; o < 4; o <<= 1) {
          s0 += __shfl_xor_sync(0xffffffffu, s0, o); q0 += __shfl_xor_sync(0xffffffffu, q0, o);
          s1 += __shfl_xor_sync(0xffffffffu, s1, o); q1 += __shfl_xor_sync(0xffffffffu, q1, o);
        }
        const float m0 = s0 * (1.f / FH), m1 = s1 * (1.f / FH);
        const float r0 = rsqrtf(fmaxf(q0 * (1.f / FH) - m0 * m0, 0.f) + 1e-5f), r1 = rsqrtf(fmaxf(q1 * (1.f / FH) - m1 * m1, 0.f) + 1e-5f);
        const float o0 = -m0 * r0, o1 = -m1 * r1;
        const uint32_t sa = sb + OFF_STG + wg * B_SLOT + (2 * wp + ((lane >> 3) & 1)) * 1792 + ((lane & 7) + (lane >> 4) * 8) * 16;
#pragma unroll
        for (int n = 0; n < 14; n += 2) {
          const float* a = acc2 + 4 * n;
          stsm4t(sa + n * 128, pack_bf16(fmaf(a[0], r0, o0), fmaf(a[1], r0, o0)), pack_bf16(fmaf(a[2], r1, o1), fmaf(a[3], r1, o1)),
                 pack_bf16(fmaf(a[4], r0, o0), fmaf(a[5], r0, o0)), pack_bf16(fmaf(a[6], r1, o1), fmaf(a[7], r1, o1)));
        }
        fence_async_smem();
        __syncwarp();
        if (lane == 0) mbar_arrive(sb + OFF_PUB + wg * 32 + 16);
#pragma unroll 1
        for (int u = 4; u < 8; u += 2) {
          issue_z1(u, 0);
          wg_wait<1>();
          if (u == 6) { release_b(); release_a(3, 2); }
          issue_z1(u + 1, 1);
          wg_wait<1>();
          release_b();
        }
        wg_wait<0>();
        release_b();
        release_a(5, 2);
#pragma unroll
        for (int e = 0; e < 56; e++) asm volatile("add.f32 %0, %1, 0f00000000;" : "=f"(acc2[e]) : "f"(acc1[e]));
        rel = NB;
      }
    }
#pragma unroll
    for (int n = 0; n < 28; n++) z1[n] = pack_bf16(acc2[2 * n], acc2[2 * n + 1]);
    wg_wait<1>();
    release_a(0, 1); release_bn(NB2);
#pragma unroll 1
    for (int u = 2; u < 32; u++) {
      mma_g2(u);
      wg_wait<1>();
      release_a(as ? as - 1 : NA - 1, 1); release_bn(NB2);
      if (++as == NA) { as = 0; aph ^= 1; }
    }
    wg_wait<0>();
    release_a(as ? as - 1 : NA - 1, 1);
    release_b();
    {
      const uint32_t bsp0 = __byte_perm(bspr0, bspr0, 0x1010), bsp1 = __byte_perm(bspr1, bspr1, 0x1010);
      mbar_wait(emptyB + 8 * (NB + wg), 0);
      const uint32_t sa = sb + OFF_STG + wg * B_SLOT + (lane >> 4) * 1024 + (16 * wp + (lane & 7) + ((lane >> 3) & 1) * 8) * 16;
#pragma unroll
      for (int n = 0; n < 14; n += 2) {
        const float* a = acc1 + 4 * n;
        stsm4(sa + n * 1024, bf2_mul(z1[2 * n], bf2_add(pack_bf16(a[0], a[1]), bsp0)), bf2_mul(z1[2 * n + 1], bf2_add(pack_bf16(a[2], a[3]), bsp1)),
              bf2_mul(z1[2 * n + 2], bf2_add(pack_bf16(a[4], a[5]), bsp0)), bf2_mul(z1[2 * n + 3], bf2_add(pack_bf16(a[6], a[7]), bsp1)));
      }
      fence_async_smem();
      __syncwarp();
      if (lane == 0) mbar_arrive(sb + OFF_PUB + wg * 32 + 24);
    }
    float acc3[28];
    uint32_t gb2[7];
#pragma unroll
    for (int n = 0; n < 7; n++) gb2[n] = lds32(sb + OFF_CSB + (112 + 4 * n + c) * 8);
#pragma unroll
    for (int u = 0; u < 4; u++) {
      const uint32_t a = __byte_perm(xres[u][0], xres[u][1], 0x5410), b = __byte_perm(xres[u][2], xres[u][3], 0x5410);
      xres[u][2] = __byte_perm(xres[u][2], xres[u][3], 0x7632); xres[u][3] = __byte_perm(xres[u][0], xres[u][1], 0x7632);
      xres[u][0] = a; xres[u][1] = b;
      asm volatile("" : "+r"(xres[u][0]), "+r"(xres[u][1]), "+r"(xres[u][2]), "+r"(xres[u][3]));
    }
    {
#pragma unroll 1
      for (int u = 0; u < 8; u++) {
        const int bf = u == 4 ? 4 : (u - 1 - (u > 4)) & 3;
        const uint32_t db = desc_lo(next_bn(NB), 16);
        mbar_wait(u ? fullG + 16 * bf + 8 * wg : sb + OFF_PUB + wg * 32 + 24, u > 5);
        const uint32_t da = desc_lo(sb + ((u & 3) ? OFF_A + bf * 28672 : OFF_STG) + wg * B_SLOT, 1024);
        wg_fence();
#pragma unroll
        for (int k = 0; k < 7; k++) wgmma_n56_tB<HI_NOSW, HI_SW128>(acc3, da + 128 * k, db + 128 * k, (u | k) != 0);
        wg_commit();
        if (u == 0) {
          wg_wait<0>();
          release_b();
          if (tw == 32) mbar_arrive(emptyG + 24);
        } else {
          wg_wait<1>();
          if (u == 2 || u == 3) { release_b(); if (tw < 2) mbar_arrive_cluster(emptyG + 8 * (u - 2), tw); }
          if (u == 3) { __syncwarp(); asm volatile("barrier.cluster.arrive.relaxed.aligned;" ::: "memory"); }
        }
      }
      wg_wait<0>();
    }
    {
      const uint32_t ob = sb + OFF_A + wg * 14336 + wp * 1792;
      uint32_t o[14];
#pragma unroll
      for (int n = 0; n < 7; n++) {
        o[2 * n] = bf2_mul(gb2[n], pack_bf16(acc3[4 * n], acc3[4 * n + 1]));
        o[2 * n + 1] = bf2_mul(gb2[n], pack_bf16(acc3[4 * n + 2], acc3[4 * n + 3]));
      }
      const uint32_t sa = ob + ((lane & 7) + ((lane >> 3) & 1) * 8) * 112 + (lane >> 4) * 16;
#pragma unroll
      for (int n = 0; n < 6; n += 2) stsm4(sa + n * 16, o[2 * n], o[2 * n + 1], o[2 * n + 2], o[2 * n + 3]);
      stsm2(ob + ((lane & 7) + ((lane >> 3) & 1) * 8) * 112 + 96, o[12], o[13]);
      __syncwarp();
#pragma unroll
      for (int u = 0; u < 4; u++) {
        const int r = g + 8 * (u & 1), cc = c + 4 * (u >> 1);
        if (cc < 7) {
          uint4 v = lds128(ob + r * 112 + cc * 16);
          v.x = bf2_add(xres[u][0], v.x); v.y = bf2_add(xres[u][1], v.y); v.z = bf2_add(xres[u][3], v.z); v.w = bf2_add(xres[u][2], v.w);
          stg128(p.out + (size_t)(ti * 128 + 16 * warp + r) * DM + 56 * tj + cc * 8, v);
        }
      }
    }
    if (tid == 0) p.s->epoch[bid] = ep;
    }
  }
}


typedef CUresult (*EncodeFn)(CUtensorMap*, CUtensorMapDataType, cuuint32_t, void*, const cuuint64_t*, const cuuint64_t*, const cuuint32_t*,
                             const cuuint32_t*, CUtensorMapInterleave, CUtensorMapSwizzle, CUtensorMapL2promotion, CUtensorMapFloatOOBfill);

}

extern "C" void kernel_launch(void* const* d_in, const int* in_sizes, int n_in, void* d_out, int out_size) {
  (void)in_sizes; (void)n_in; (void)out_size;
  static EncodeFn enc = nullptr;
  static Scratch* scr = nullptr;
  if (!enc) {
    cudaGetSymbolAddress((void**)&scr, g_scr);
    void* fn = nullptr;
    cudaDriverEntryPointQueryResult qr;
    cudaGetDriverEntryPoint("cuTensorMapEncodeTiled", &fn, cudaEnableDefault, &qr);
    enc = (EncodeFn)fn;
    cudaFuncSetAttribute(fused_block_kernel, cudaFuncAttributeMaxDynamicSharedMemorySize, SMEM_BYTES);
  }
  Params p;
  p.s = scr; p.zero = 0; p.pad = 0;
  p.x = (const __nv_bfloat16*)d_in[0];
  p.a_re = (const __nv_bfloat16*)d_in[1]; p.a_im = (const __nv_bfloat16*)d_in[2];
  p.b_re = (const __nv_bfloat16*)d_in[3]; p.b_im = (const __nv_bfloat16*)d_in[4];
  p.c_re = (const __nv_bfloat16*)d_in[5]; p.c_im = (const __nv_bfloat16*)d_in[6];
  p.log_dt = (const __nv_bfloat16*)d_in[7]; p.dskip = (const __nv_bfloat16*)d_in[8];
  p.w_sp = (const __nv_bfloat16*)d_in[11];
  p.b_sp = (const __nv_bfloat16*)d_in[12]; p.w_out = (const __nv_bfloat16*)d_in[13];
  p.cvec = (const __nv_bfloat16*)d_in[14];
  p.out = (__nv_bfloat16*)d_out;
  Maps m;
  auto make = [&](CUtensorMap* tm, void* base, uint64_t cols, uint64_t rows, uint32_t bc, uint32_t br, CUtensorMapSwizzle sw) {
    cuuint64_t gd[2] = {cols, rows}, gs[1] = {cols * 2};
    cuuint32_t box[2] = {bc, br}, es[2] = {1, 1};
    enc(tm, CU_TENSOR_MAP_DATA_TYPE_BFLOAT16, 2, base, gd, gs, box, es, CU_TENSOR_MAP_INTERLEAVE_NONE, sw,
        CU_TENSOR_MAP_L2_PROMOTION_L2_128B, CU_TENSOR_MAP_FLOAT_OOB_FILL_NONE);
  };
  make(&m.wsp, d_in[11], SEQ, SEQ, 64, 64, CU_TENSOR_MAP_SWIZZLE_128B);
  make(&m.wout, d_in[13], DM, FH, 64, 112, CU_TENSOR_MAP_SWIZZLE_128B);
  make(&m.wmod, d_in[15], 6 * DM, DM, 56, 224, CU_TENSOR_MAP_SWIZZLE_NONE);
  make(&m.wmod8, d_in[15], 6 * DM, DM, 8, 224, CU_TENSOR_MAP_SWIZZLE_NONE);
  make(&m.win, d_in[10], 4 * FF, DM / 4, 112, 112, CU_TENSOR_MAP_SWIZZLE_NONE);
  {
    cuuint64_t gd[2] = {SEQ, DM}, gs[1] = {SEQ * 4};
    cuuint32_t box[2] = {16, 224}, es[2] = {1, 1};
    enc(&m.nx, CU_TENSOR_MAP_DATA_TYPE_UINT32, 2, scr->nx, gd, gs, box, es, CU_TENSOR_MAP_INTERLEAVE_NONE, CU_TENSOR_MAP_SWIZZLE_64B,
        CU_TENSOR_MAP_L2_PROMOTION_NONE, CU_TENSOR_MAP_FLOAT_OOB_FILL_NONE);
  }
  {
    cuuint64_t gd[5] = {64, 112, 2, 4, 16}, gs[4] = {128, 14336, 28672, 114688};
    cuuint32_t box[5] = {64, 1, 2, 1, 16}, es[5] = {1, 1, 1, 1, 1};
    enc(&m.x1, CU_TENSOR_MAP_DATA_TYPE_BFLOAT16, 5, scr->x1, gd, gs, box, es, CU_TENSOR_MAP_INTERLEAVE_NONE, CU_TENSOR_MAP_SWIZZLE_NONE,
        CU_TENSOR_MAP_L2_PROMOTION_NONE, CU_TENSOR_MAP_FLOAT_OOB_FILL_NONE);
  }
  fused_block_kernel<<<NCTA, NTHREADS, SMEM_BYTES>>>(p, m);
}
```
